```python
import torch

def _softmax(x, axis=-1):
    return torch.softmax(x, dim=axis)
def _gelu(x):
    return torch.nn.functional.gelu(x, approximate="tanh")
def _silu(x):
    return torch.nn.functional.silu(x)
def _sigmoid(x):
    return torch.sigmoid(x)
def _layernorm(x, axis=-1, eps=1e-5):
    m = x.mean(dim=axis, keepdim=True)
    v = x.var(dim=axis, keepdim=True, unbiased=False)
    return (x - m) / torch.sqrt(v + eps)
def _scatter_add(tgt, idx, src, axis=0):
    return tgt.clone().index_add_(axis, idx, src)
def _segment_sum(src, seg, n):
    out = torch.zeros((n,) + src.shape[1:], dtype=src.dtype)
    return out.index_add_(0, seg, src)
def _pad(x, pw):
    flat = tuple(v for pair in reversed(pw) for v in pair)
    return torch.nn.functional.pad(x, flat)

kernel_name = 'gated_mix__ssm_conv_s4__linear_attn_block__prompt'

def setup_inputs():

    _w = (lambda a: (lambda t: t.to(torch.bfloat16) if t.is_floating_point() else t)(torch.as_tensor(a)))
    def _A_setup():
        B, L, D, N = 1, 2048, 640, 192
        A_re = -(lambda _x: torch.exp(torch.as_tensor(_x)))((lambda *s: torch.randn(*s, dtype=torch.bfloat16) * 6.4)(D, N))
        A_im = torch.pi * (lambda *s: torch.randn(*s, dtype=torch.bfloat16) * 0.05)(D, N)
        B_re = (lambda *s: torch.randn(*s, dtype=torch.bfloat16) * 0.1)(D, N)
        B_im = (lambda *s: torch.randn(*s, dtype=torch.bfloat16) * 0.1)(D, N)
        C_re = (lambda *s: torch.randn(*s, dtype=torch.bfloat16) * 0.1)(D, N)
        C_im = (lambda *s: torch.randn(*s, dtype=torch.bfloat16) * 0.1)(D, N)
        log_dt = (lambda *s: torch.randn(*s, dtype=torch.bfloat16) * 0.05)(D) * 0.5 - 4.0
        Dskip = (lambda *s: torch.randn(*s, dtype=torch.bfloat16) * 0.05)(D)
        return {
            "u": _w((lambda *s: torch.randn(*s, dtype=torch.bfloat16) * 0.05)(B, L, D)),
            "A_re": _w(A_re),
            "A_im": _w(A_im),
            "B_re": _w(B_re),
            "B_im": _w(B_im),
            "C_re": _w(C_re),
            "C_im": _w(C_im),
            "log_dt": _w(log_dt),
            "Dskip": _w(Dskip),
        }
    _A_in = _A_setup()

    def _B_setup():
        B, S, D = 1, 2048, 640
        return {
            "x": _w((lambda *s: torch.randn(*s, dtype=torch.bfloat16) * 0.05)(B, S, D)),
            "wqkv": _w((lambda *s: torch.randn(*s, dtype=torch.bfloat16) * 0.4)(D, 3 * D)),
            "wo": _w((lambda *s: torch.randn(*s, dtype=torch.bfloat16) * 0.05)(D, D)),
        }
    _B_in = _B_setup()

    return {
        "A_u": _A_in["u"],
        "A_A_re": _A_in["A_re"],
        "A_A_im": _A_in["A_im"],
        "A_B_re": _A_in["B_re"],
        "A_B_im": _A_in["B_im"],
        "A_C_re": _A_in["C_re"],
        "A_C_im": _A_in["C_im"],
        "A_log_dt": _A_in["log_dt"],
        "A_Dskip": _A_in["Dskip"],
        "B_x": _B_in["x"],
        "B_wqkv": _B_in["wqkv"],
        "B_wo": _B_in["wo"],
        "gate_w": _w((lambda *s: torch.randn(*s, dtype=torch.bfloat16) * 0.05)(640) * 16.0),
    }

def reference(A_u, A_A_re, A_A_im, A_B_re, A_B_im, A_C_re, A_C_im, A_log_dt, A_Dskip, B_x, B_wqkv, B_wo, gate_w):
    def _A_ref(u, A_re, A_im, B_re, B_im, C_re, C_im, log_dt, Dskip):
        Bsz, L, D = u.shape
        dt = torch.exp(log_dt)[:, None]
        A = A_re + 1j * A_im
        Bc = B_re + 1j * B_im
        Cc = C_re + 1j * C_im
        logdA = dt * A
        dB = dt * Bc
        l = (lambda x, dt: x.to(dt))(torch.arange(L), A_re.dtype)
        P = torch.exp(logdA[:, :, None] * l[None, None, :])
        K = torch.einsum("dn,dnl,dn->dl", Cc, P, dB).real
        L2 = 2 * L
        Kp = _pad(K, ((0, 0), (0, L)))
        up = (lambda x, *d: x.permute(*d))(u, 0, 2, 1)
        up = _pad(up, ((0, 0), (0, 0), (0, L)))
        Kf = (lambda x, axes=(-2,-1): torch.fft.rfft2(x.float(), dim=axes))(Kp[:, None, :], axes=(-2, -1))
        Uf = (lambda x, axes=(-2,-1): torch.fft.rfft2(x.float(), dim=axes))(up[:, :, None, :], axes=(-2, -1))
        Yf = Uf * Kf[None, :, :, :]
        y = (lambda x, s, axes=(-2,-1): torch.fft.irfft2(x, s=s, dim=axes).to(torch.bfloat16))(Yf, (1, L2), axes=(-2, -1))[:, :, 0, :L]
        y = (lambda x, *d: x.permute(*d))(y, 0, 2, 1) + u * Dskip[None, None, :]
        return y

    def _B_ref(x, wqkv, wo):
        B, S, D = x.shape
        H = 32; Dh = D // H
        qkv = (lambda x, *d: x.permute(*d))((x @ wqkv).reshape(B, S, 3, H, Dh), 2, 0, 3, 1, 4)
        q, k, v = qkv[0], qkv[1], qkv[2]
        phi = lambda t: torch.where(t > 0, t + 1, torch.exp(t)) + 1e-6
        pq, pk = phi(q), phi(k)
        kv = torch.einsum("bhsd,bhse->bhde", pk, v)
        z = torch.einsum("bhsd->bhd", pk)
        num = torch.einsum("bhqd,bhde->bhqe", pq, kv)
        den = torch.einsum("bhqd,bhd->bhq", pq, z)[..., None] + 1e-6
        o = num / den
        return (lambda x, *d: x.permute(*d))(o, 0, 2, 1, 3).reshape(B, S, D) @ wo

    x = A_u
    g = _sigmoid((x * gate_w).sum(-1, keepdims=True))
    a = _A_ref(x, A_A_re, A_A_im, A_B_re, A_B_im, A_C_re, A_C_im, A_log_dt, A_Dskip)
    b = _B_ref(x, B_wqkv, B_wo)
    return g * a + (1 - g) * b
```

```cpp
#include <cuda_runtime.h>
#include <cuda_bf16.h>
#include <cuda.h>
#include <cudaTypedefs.h>
#include <stdint.h>

template<int OFF> struct Lin { __host__ __device__ static constexpr int at(int i){ return OFF+i; } };
template<int OFF,int CH,int ST> struct Chk { __host__ __device__ static constexpr int at(int i){ return OFF+(i/CH)*ST+(i%CH); } };
template<int TB,class IM,int BO,int BH,int SC,int SZ> __device__ __forceinline__ void wgmma_rs_n32(float (&d)[SZ], uint32_t a0, uint32_t a1, uint32_t a2, uint32_t a3, uint32_t blo) {
  asm volatile("{\n.reg .pred p;\n.reg .b32 u;\n.reg .b64 db;\nsetp.ne.b32 p, %24, 0;\nadd.u32 u, %20, %21;\nmov.b64 db, {u, %22};\nwgmma.mma_async.sync.aligned.m64n32k16.f32.bf16.bf16 {%0, %1, %2, %3, %4, %5, %6, %7, %8, %9, %10, %11, %12, %13, %14, %15}, {%16,%17,%18,%19}, db, p, 1, 1, %23;\n}\n"
   : "+f"(d[IM::at(0)]), "+f"(d[IM::at(1)]), "+f"(d[IM::at(2)]), "+f"(d[IM::at(3)]), "+f"(d[IM::at(4)]), "+f"(d[IM::at(5)]), "+f"(d[IM::at(6)]), "+f"(d[IM::at(7)]), "+f"(d[IM::at(8)]), "+f"(d[IM::at(9)]), "+f"(d[IM::at(10)]), "+f"(d[IM::at(11)]), "+f"(d[IM::at(12)]), "+f"(d[IM::at(13)]), "+f"(d[IM::at(14)]), "+f"(d[IM::at(15)])
   : "r"(a0), "r"(a1), "r"(a2), "r"(a3), "r"(blo), "n"(BO), "n"(BH), "n"(TB), "n"(SC));
}
template<int TB,class IM,int BO,int BH,int SC,int SZ> __device__ __forceinline__ void wgmma_rs_n48(float (&d)[SZ], uint32_t a0, uint32_t a1, uint32_t a2, uint32_t a3, uint32_t blo) {
  asm volatile("{\n.reg .pred p;\n.reg .b32 u;\n.reg .b64 db;\nsetp.ne.b32 p, %32, 0;\nadd.u32 u, %28, %29;\nmov.b64 db, {u, %30};\nwgmma.mma_async.sync.aligned.m64n48k16.f32.bf16.bf16 {%0, %1, %2, %3, %4, %5, %6, %7, %8, %9, %10, %11, %12, %13, %14, %15, %16, %17, %18, %19, %20, %21, %22, %23}, {%24,%25,%26,%27}, db, p, 1, 1, %31;\n}\n"
   : "+f"(d[IM::at(0)]), "+f"(d[IM::at(1)]), "+f"(d[IM::at(2)]), "+f"(d[IM::at(3)]), "+f"(d[IM::at(4)]), "+f"(d[IM::at(5)]), "+f"(d[IM::at(6)]), "+f"(d[IM::at(7)]), "+f"(d[IM::at(8)]), "+f"(d[IM::at(9)]), "+f"(d[IM::at(10)]), "+f"(d[IM::at(11)]), "+f"(d[IM::at(12)]), "+f"(d[IM::at(13)]), "+f"(d[IM::at(14)]), "+f"(d[IM::at(15)]), "+f"(d[IM::at(16)]), "+f"(d[IM::at(17)]), "+f"(d[IM::at(18)]), "+f"(d[IM::at(19)]), "+f"(d[IM::at(20)]), "+f"(d[IM::at(21)]), "+f"(d[IM::at(22)]), "+f"(d[IM::at(23)])
   : "r"(a0), "r"(a1), "r"(a2), "r"(a3), "r"(blo), "n"(BO), "n"(BH), "n"(TB), "n"(SC));
}
template<int TB,class IM,int BO,int BH,int SC,int SZ> __device__ __forceinline__ void wgmma_rs_n64(float (&d)[SZ], uint32_t a0, uint32_t a1, uint32_t a2, uint32_t a3, uint32_t blo) {
  asm volatile("{\n.reg .pred p;\n.reg .b32 u;\n.reg .b64 db;\nsetp.ne.b32 p, %40, 0;\nadd.u32 u, %36, %37;\nmov.b64 db, {u, %38};\nwgmma.mma_async.sync.aligned.m64n64k16.f32.bf16.bf16 {%0, %1, %2, %3, %4, %5, %6, %7, %8, %9, %10, %11, %12, %13, %14, %15, %16, %17, %18, %19, %20, %21, %22, %23, %24, %25, %26, %27, %28, %29, %30, %31}, {%32,%33,%34,%35}, db, p, 1, 1, %39;\n}\n"
   : "+f"(d[IM::at(0)]), "+f"(d[IM::at(1)]), "+f"(d[IM::at(2)]), "+f"(d[IM::at(3)]), "+f"(d[IM::at(4)]), "+f"(d[IM::at(5)]), "+f"(d[IM::at(6)]), "+f"(d[IM::at(7)]), "+f"(d[IM::at(8)]), "+f"(d[IM::at(9)]), "+f"(d[IM::at(10)]), "+f"(d[IM::at(11)]), "+f"(d[IM::at(12)]), "+f"(d[IM::at(13)]), "+f"(d[IM::at(14)]), "+f"(d[IM::at(15)]), "+f"(d[IM::at(16)]), "+f"(d[IM::at(17)]), "+f"(d[IM::at(18)]), "+f"(d[IM::at(19)]), "+f"(d[IM::at(20)]), "+f"(d[IM::at(21)]), "+f"(d[IM::at(22)]), "+f"(d[IM::at(23)]), "+f"(d[IM::at(24)]), "+f"(d[IM::at(25)]), "+f"(d[IM::at(26)]), "+f"(d[IM::at(27)]), "+f"(d[IM::at(28)]), "+f"(d[IM::at(29)]), "+f"(d[IM::at(30)]), "+f"(d[IM::at(31)])
   : "r"(a0), "r"(a1), "r"(a2), "r"(a3), "r"(blo), "n"(BO), "n"(BH), "n"(TB), "n"(SC));
}
template<int TB,class IM,int BO,int BH,int SC,int SZ> __device__ __forceinline__ void wgmma_rs_n80(float (&d)[SZ], uint32_t a0, uint32_t a1, uint32_t a2, uint32_t a3, uint32_t blo) {
  asm volatile("{\n.reg .pred p;\n.reg .b32 u;\n.reg .b64 db;\nsetp.ne.b32 p, %48, 0;\nadd.u32 u, %44, %45;\nmov.b64 db, {u, %46};\nwgmma.mma_async.sync.aligned.m64n80k16.f32.bf16.bf16 {%0, %1, %2, %3, %4, %5, %6, %7, %8, %9, %10, %11, %12, %13, %14, %15, %16, %17, %18, %19, %20, %21, %22, %23, %24, %25, %26, %27, %28, %29, %30, %31, %32, %33, %34, %35, %36, %37, %38, %39}, {%40,%41,%42,%43}, db, p, 1, 1, %47;\n}\n"
   : "+f"(d[IM::at(0)]), "+f"(d[IM::at(1)]), "+f"(d[IM::at(2)]), "+f"(d[IM::at(3)]), "+f"(d[IM::at(4)]), "+f"(d[IM::at(5)]), "+f"(d[IM::at(6)]), "+f"(d[IM::at(7)]), "+f"(d[IM::at(8)]), "+f"(d[IM::at(9)]), "+f"(d[IM::at(10)]), "+f"(d[IM::at(11)]), "+f"(d[IM::at(12)]), "+f"(d[IM::at(13)]), "+f"(d[IM::at(14)]), "+f"(d[IM::at(15)]), "+f"(d[IM::at(16)]), "+f"(d[IM::at(17)]), "+f"(d[IM::at(18)]), "+f"(d[IM::at(19)]), "+f"(d[IM::at(20)]), "+f"(d[IM::at(21)]), "+f"(d[IM::at(22)]), "+f"(d[IM::at(23)]), "+f"(d[IM::at(24)]), "+f"(d[IM::at(25)]), "+f"(d[IM::at(26)]), "+f"(d[IM::at(27)]), "+f"(d[IM::at(28)]), "+f"(d[IM::at(29)]), "+f"(d[IM::at(30)]), "+f"(d[IM::at(31)]), "+f"(d[IM::at(32)]), "+f"(d[IM::at(33)]), "+f"(d[IM::at(34)]), "+f"(d[IM::at(35)]), "+f"(d[IM::at(36)]), "+f"(d[IM::at(37)]), "+f"(d[IM::at(38)]), "+f"(d[IM::at(39)])
   : "r"(a0), "r"(a1), "r"(a2), "r"(a3), "r"(blo), "n"(BO), "n"(BH), "n"(TB), "n"(SC));
}
template<int TB,class IM,int BO,int BH,int SC,int SZ> __device__ __forceinline__ void wgmma_rs_n192(float (&d)[SZ], uint32_t a0, uint32_t a1, uint32_t a2, uint32_t a3, uint32_t blo) {
  asm volatile("{\n.reg .pred p;\n.reg .b32 u;\n.reg .b64 db;\nsetp.ne.b32 p, %104, 0;\nadd.u32 u, %100, %101;\nmov.b64 db, {u, %102};\nwgmma.mma_async.sync.aligned.m64n192k16.f32.bf16.bf16 {%0, %1, %2, %3, %4, %5, %6, %7, %8, %9, %10, %11, %12, %13, %14, %15, %16, %17, %18, %19, %20, %21, %22, %23, %24, %25, %26, %27, %28, %29, %30, %31, %32, %33, %34, %35, %36, %37, %38, %39, %40, %41, %42, %43, %44, %45, %46, %47, %48, %49, %50, %51, %52, %53, %54, %55, %56, %57, %58, %59, %60, %61, %62, %63, %64, %65, %66, %67, %68, %69, %70, %71, %72, %73, %74, %75, %76, %77, %78, %79, %80, %81, %82, %83, %84, %85, %86, %87, %88, %89, %90, %91, %92, %93, %94, %95}, {%96,%97,%98,%99}, db, p, 1, 1, %103;\n}\n"
   : "+f"(d[IM::at(0)]), "+f"(d[IM::at(1)]), "+f"(d[IM::at(2)]), "+f"(d[IM::at(3)]), "+f"(d[IM::at(4)]), "+f"(d[IM::at(5)]), "+f"(d[IM::at(6)]), "+f"(d[IM::at(7)]), "+f"(d[IM::at(8)]), "+f"(d[IM::at(9)]), "+f"(d[IM::at(10)]), "+f"(d[IM::at(11)]), "+f"(d[IM::at(12)]), "+f"(d[IM::at(13)]), "+f"(d[IM::at(14)]), "+f"(d[IM::at(15)]), "+f"(d[IM::at(16)]), "+f"(d[IM::at(17)]), "+f"(d[IM::at(18)]), "+f"(d[IM::at(19)]), "+f"(d[IM::at(20)]), "+f"(d[IM::at(21)]), "+f"(d[IM::at(22)]), "+f"(d[IM::at(23)]), "+f"(d[IM::at(24)]), "+f"(d[IM::at(25)]), "+f"(d[IM::at(26)]), "+f"(d[IM::at(27)]), "+f"(d[IM::at(28)]), "+f"(d[IM::at(29)]), "+f"(d[IM::at(30)]), "+f"(d[IM::at(31)]), "+f"(d[IM::at(32)]), "+f"(d[IM::at(33)]), "+f"(d[IM::at(34)]), "+f"(d[IM::at(35)]), "+f"(d[IM::at(36)]), "+f"(d[IM::at(37)]), "+f"(d[IM::at(38)]), "+f"(d[IM::at(39)]), "+f"(d[IM::at(40)]), "+f"(d[IM::at(41)]), "+f"(d[IM::at(42)]), "+f"(d[IM::at(43)]), "+f"(d[IM::at(44)]), "+f"(d[IM::at(45)]), "+f"(d[IM::at(46)]), "+f"(d[IM::at(47)]), "+f"(d[IM::at(48)]), "+f"(d[IM::at(49)]), "+f"(d[IM::at(50)]), "+f"(d[IM::at(51)]), "+f"(d[IM::at(52)]), "+f"(d[IM::at(53)]), "+f"(d[IM::at(54)]), "+f"(d[IM::at(55)]), "+f"(d[IM::at(56)]), "+f"(d[IM::at(57)]), "+f"(d[IM::at(58)]), "+f"(d[IM::at(59)]), "+f"(d[IM::at(60)]), "+f"(d[IM::at(61)]), "+f"(d[IM::at(62)]), "+f"(d[IM::at(63)]), "+f"(d[IM::at(64)]), "+f"(d[IM::at(65)]), "+f"(d[IM::at(66)]), "+f"(d[IM::at(67)]), "+f"(d[IM::at(68)]), "+f"(d[IM::at(69)]), "+f"(d[IM::at(70)]), "+f"(d[IM::at(71)]), "+f"(d[IM::at(72)]), "+f"(d[IM::at(73)]), "+f"(d[IM::at(74)]), "+f"(d[IM::at(75)]), "+f"(d[IM::at(76)]), "+f"(d[IM::at(77)]), "+f"(d[IM::at(78)]), "+f"(d[IM::at(79)]), "+f"(d[IM::at(80)]), "+f"(d[IM::at(81)]), "+f"(d[IM::at(82)]), "+f"(d[IM::at(83)]), "+f"(d[IM::at(84)]), "+f"(d[IM::at(85)]), "+f"(d[IM::at(86)]), "+f"(d[IM::at(87)]), "+f"(d[IM::at(88)]), "+f"(d[IM::at(89)]), "+f"(d[IM::at(90)]), "+f"(d[IM::at(91)]), "+f"(d[IM::at(92)]), "+f"(d[IM::at(93)]), "+f"(d[IM::at(94)]), "+f"(d[IM::at(95)])
   : "r"(a0), "r"(a1), "r"(a2), "r"(a3), "r"(blo), "n"(BO), "n"(BH), "n"(TB), "n"(SC));
}
template<int TA,int TB,class IM,int AO,int AH,int BO,int BH,int SC,int SZ> __device__ __forceinline__ void wgmma_ss_n40(float (&d)[SZ], uint32_t alo, uint32_t blo) {
  asm volatile("{\n.reg .pred p;\n.reg .b32 t,u;\n.reg .b64 da,db;\nsetp.ne.b32 p, %28, 0;\nadd.u32 t, %20, %22;\nmov.b64 da, {t, %23};\nadd.u32 u, %21, %24;\nmov.b64 db, {u, %25};\nwgmma.mma_async.sync.aligned.m64n40k16.f32.bf16.bf16 {%0, %1, %2, %3, %4, %5, %6, %7, %8, %9, %10, %11, %12, %13, %14, %15, %16, %17, %18, %19}, da, db, p, 1, 1, %26, %27;\n}\n"
   : "+f"(d[IM::at(0)]), "+f"(d[IM::at(1)]), "+f"(d[IM::at(2)]), "+f"(d[IM::at(3)]), "+f"(d[IM::at(4)]), "+f"(d[IM::at(5)]), "+f"(d[IM::at(6)]), "+f"(d[IM::at(7)]), "+f"(d[IM::at(8)]), "+f"(d[IM::at(9)]), "+f"(d[IM::at(10)]), "+f"(d[IM::at(11)]), "+f"(d[IM::at(12)]), "+f"(d[IM::at(13)]), "+f"(d[IM::at(14)]), "+f"(d[IM::at(15)]), "+f"(d[IM::at(16)]), "+f"(d[IM::at(17)]), "+f"(d[IM::at(18)]), "+f"(d[IM::at(19)])
   : "r"(alo), "r"(blo), "n"(AO), "n"(AH), "n"(BO), "n"(BH), "n"(TA), "n"(TB), "n"(SC));
}
template<int TA,int TB,class IM,int AO,int AH,int BO,int BH,int SC,int SZ> __device__ __forceinline__ void wgmma_ss_n48(float (&d)[SZ], uint32_t alo, uint32_t blo) {
  asm volatile("{\n.reg .pred p;\n.reg .b32 t,u;\n.reg .b64 da,db;\nsetp.ne.b32 p, %32, 0;\nadd.u32 t, %24, %26;\nmov.b64 da, {t, %27};\nadd.u32 u, %25, %28;\nmov.b64 db, {u, %29};\nwgmma.mma_async.sync.aligned.m64n48k16.f32.bf16.bf16 {%0, %1, %2, %3, %4, %5, %6, %7, %8, %9, %10, %11, %12, %13, %14, %15, %16, %17, %18, %19, %20, %21, %22, %23}, da, db, p, 1, 1, %30, %31;\n}\n"
   : "+f"(d[IM::at(0)]), "+f"(d[IM::at(1)]), "+f"(d[IM::at(2)]), "+f"(d[IM::at(3)]), "+f"(d[IM::at(4)]), "+f"(d[IM::at(5)]), "+f"(d[IM::at(6)]), "+f"(d[IM::at(7)]), "+f"(d[IM::at(8)]), "+f"(d[IM::at(9)]), "+f"(d[IM::at(10)]), "+f"(d[IM::at(11)]), "+f"(d[IM::at(12)]), "+f"(d[IM::at(13)]), "+f"(d[IM::at(14)]), "+f"(d[IM::at(15)]), "+f"(d[IM::at(16)]), "+f"(d[IM::at(17)]), "+f"(d[IM::at(18)]), "+f"(d[IM::at(19)]), "+f"(d[IM::at(20)]), "+f"(d[IM::at(21)]), "+f"(d[IM::at(22)]), "+f"(d[IM::at(23)])
   : "r"(alo), "r"(blo), "n"(AO), "n"(AH), "n"(BO), "n"(BH), "n"(TA), "n"(TB), "n"(SC));
}
template<int TA,int TB,class IM,int AO,int AH,int BO,int BH,int SC,int SZ> __device__ __forceinline__ void wgmma_ss_n80(float (&d)[SZ], uint32_t alo, uint32_t blo) {
  asm volatile("{\n.reg .pred p;\n.reg .b32 t,u;\n.reg .b64 da,db;\nsetp.ne.b32 p, %48, 0;\nadd.u32 t, %40, %42;\nmov.b64 da, {t, %43};\nadd.u32 u, %41, %44;\nmov.b64 db, {u, %45};\nwgmma.mma_async.sync.aligned.m64n80k16.f32.bf16.bf16 {%0, %1, %2, %3, %4, %5, %6, %7, %8, %9, %10, %11, %12, %13, %14, %15, %16, %17, %18, %19, %20, %21, %22, %23, %24, %25, %26, %27, %28, %29, %30, %31, %32, %33, %34, %35, %36, %37, %38, %39}, da, db, p, 1, 1, %46, %47;\n}\n"
   : "+f"(d[IM::at(0)]), "+f"(d[IM::at(1)]), "+f"(d[IM::at(2)]), "+f"(d[IM::at(3)]), "+f"(d[IM::at(4)]), "+f"(d[IM::at(5)]), "+f"(d[IM::at(6)]), "+f"(d[IM::at(7)]), "+f"(d[IM::at(8)]), "+f"(d[IM::at(9)]), "+f"(d[IM::at(10)]), "+f"(d[IM::at(11)]), "+f"(d[IM::at(12)]), "+f"(d[IM::at(13)]), "+f"(d[IM::at(14)]), "+f"(d[IM::at(15)]), "+f"(d[IM::at(16)]), "+f"(d[IM::at(17)]), "+f"(d[IM::at(18)]), "+f"(d[IM::at(19)]), "+f"(d[IM::at(20)]), "+f"(d[IM::at(21)]), "+f"(d[IM::at(22)]), "+f"(d[IM::at(23)]), "+f"(d[IM::at(24)]), "+f"(d[IM::at(25)]), "+f"(d[IM::at(26)]), "+f"(d[IM::at(27)]), "+f"(d[IM::at(28)]), "+f"(d[IM::at(29)]), "+f"(d[IM::at(30)]), "+f"(d[IM::at(31)]), "+f"(d[IM::at(32)]), "+f"(d[IM::at(33)]), "+f"(d[IM::at(34)]), "+f"(d[IM::at(35)]), "+f"(d[IM::at(36)]), "+f"(d[IM::at(37)]), "+f"(d[IM::at(38)]), "+f"(d[IM::at(39)])
   : "r"(alo), "r"(blo), "n"(AO), "n"(AH), "n"(BO), "n"(BH), "n"(TA), "n"(TB), "n"(SC));
}
template<int N,int TA,int TB,class IM,int AO,int AH,int BO,int BH,int SC,int SZ> __device__ __forceinline__ void wgmma_ss(float (&d)[SZ], uint32_t alo, uint32_t blo) {
  if constexpr (N==40) wgmma_ss_n40<TA,TB,IM,AO,AH,BO,BH,SC>(d,alo,blo);
  if constexpr (N==48) wgmma_ss_n48<TA,TB,IM,AO,AH,BO,BH,SC>(d,alo,blo);
  if constexpr (N==80) wgmma_ss_n80<TA,TB,IM,AO,AH,BO,BH,SC>(d,alo,blo);
}
template<int N,int TB,class IM,int BO,int BH,int SC,int SZ> __device__ __forceinline__ void wgmma_rs(float (&d)[SZ], const uint32_t (&a)[4], uint32_t blo) {
  if constexpr (N==32) wgmma_rs_n32<TB,IM,BO,BH,SC>(d,a[0],a[1],a[2],a[3],blo);
  if constexpr (N==48) wgmma_rs_n48<TB,IM,BO,BH,SC>(d,a[0],a[1],a[2],a[3],blo);
  if constexpr (N==64) wgmma_rs_n64<TB,IM,BO,BH,SC>(d,a[0],a[1],a[2],a[3],blo);
  if constexpr (N==80) wgmma_rs_n80<TB,IM,BO,BH,SC>(d,a[0],a[1],a[2],a[3],blo);
  if constexpr (N==192) wgmma_rs_n192<TB,IM,BO,BH,SC>(d,a[0],a[1],a[2],a[3],blo);
}
__host__ __device__ constexpr int DOFF(int bytes,int lbo){ return (bytes>>4) | ((lbo>>4)<<16); }
__host__ __device__ constexpr int DHI(int sbo,int swz){ return (sbo>>4) | (swz<<30); }

#define TRAPS(P, CODE) "@" P " trap;\n"
#define TRAPC(CODE) __trap()
namespace gm {

extern __shared__ __align__(1024) char smem_raw[];
__device__ uint32_t g_epoch;
__device__ __align__(128) uint4 g_kp[8 * 16 * 16 * 30];
__device__ __align__(128) uint4 g_kf[8 * 480];
__device__ __align__(1024) uint4 g_xT[640 * 256];
__device__ __align__(1024) uint4 g_y[16 * 640 * 16];
__device__ __align__(1024) uint4 g_o[16 * 8 * 1280];
__device__ __align__(128) uint32_t g_gate[2048];
__device__ __align__(1024) uint4 g_wo[8 * 6400];
__device__ __align__(128) uint32_t g_fw[8 * 32];
__device__ __align__(128) uint32_t g_fx[2 * 128];
__device__ __align__(128) uint32_t g_fo[16 * 8 * 8];

constexpr uint32_t STB = 47104;
constexpr uint32_t OFF_PKV = 75776;
constexpr uint32_t OFF_OS = 102400;
constexpr uint32_t OFF_KY = 141312;
constexpr uint32_t OFF_XR = 167936;
constexpr uint32_t OFF_GW = 171008;
constexpr uint32_t OFF_K0 = 172288;
constexpr uint32_t OFF_GP = 172416;
constexpr uint32_t OFF_KX = 173056;
constexpr uint32_t OFF_KVB = 122880;
constexpr uint32_t OFF_TB = OFF_KX + 11520, TBS = 3008;
constexpr uint32_t OFF_UT = 199680, UTS = 4352;
constexpr uint32_t OFF_KB = 221440, KBS = 1296;
constexpr uint32_t OFF_BAR = 227920, OFF_YT = OFF_BAR - 20480;
constexpr uint32_t OFF_EP = OFF_BAR + 8 * 44;
constexpr uint32_t OFF_PROF = 228352;
constexpr uint32_t SMEM_BYTES = 228864;

enum { B_FULL = 0, B_EMPTY = 3, B_SF = 6, B_KVR, B_ORDY, B_OE, B_T0 = 12, B_KVB, B_T1, B_W2, B_YD, B_LX, B_KF, B_KE = B_KF + 2, B_K0 = B_KE + 2, B_SLAB, B_WOT, B_ZP, B_UTL, B_UT, B_WO, B_YT, B_EP, B_OF, B_NUM = B_OF + 7, B_PRM = B_NUM };

__host__ __device__ constexpr int bar_count(int b) { return b < B_EMPTY || b == B_OE ? 1 : b == B_OE + 2 ? 16 : b == B_OE + 1 ? 12 : b < B_T0 ? 8 : b < B_K0 ? 4 : b == B_K0 ? 6 : 1; }

#define PROFX(g, t, id) do { } while (0)
#define PROFT(t, id) do { } while (0)
#define PROF(id) do { } while (0)

__device__ __forceinline__ uint32_t smem_u32(const void* p) { return (uint32_t)__cvta_generic_to_shared(p); }
__device__ __forceinline__ void mbar_init(uint32_t bar, uint32_t cnt) { asm volatile("mbarrier.init.shared::cta.b64 [%0], %1;" ::"r"(bar), "r"(cnt) : "memory"); }
__device__ __forceinline__ void mbar_expect_tx(uint32_t bar, uint32_t bytes) { asm volatile("mbarrier.arrive.expect_tx.shared::cta.b64 _, [%0], %1;" ::"r"(bar), "r"(bytes) : "memory"); }
__device__ __forceinline__ void mbar_arrive(uint32_t bar) { asm volatile("mbarrier.arrive.shared::cta.b64 _, [%0];" ::"r"(bar) : "memory"); }
__device__ __forceinline__ bool mbar_test(uint32_t bar, uint32_t parity) {
  uint32_t ok;
  asm volatile("{\n.reg .pred p;\nmbarrier.test_wait.parity.shared::cta.b64 p, [%1], %2;\nselp.u32 %0,1,0,p;\n}" : "=r"(ok) : "r"(bar), "r"(parity) : "memory");
  return ok;
}
__device__ __forceinline__ void mbar_wait(uint32_t bar, uint32_t parity) {
  asm volatile("{\n.reg .pred p,q;\n.reg .u32 c;\nmov.u32 c,0;\nL%=:\nmbarrier.try_wait.parity.shared::cta.b64 p, [%0], %1;\n@p bra D%=;\n"
               "add.u32 c,c,1;\nsetp.gt.u32 q,c,1048576;\n" TRAPS("q", "%0") "bra L%=;\nD%=:\n}" ::"r"(bar), "r"(parity) : "memory");
}
__device__ __forceinline__ void bulk_g2s(uint32_t dst, const void* src, uint32_t bytes, uint32_t bar) {
  asm volatile("cp.async.bulk.shared::cluster.global.mbarrier::complete_tx::bytes [%0], [%1], %2, [%3];" ::"r"(dst), "l"(src), "r"(bytes), "r"(bar) : "memory");
}
__device__ __forceinline__ void bulk_g2s_mc(uint32_t dst, const void* src, uint32_t bytes, uint32_t bar) {
  asm volatile("cp.async.bulk.shared::cluster.global.mbarrier::complete_tx::bytes.multicast::cluster [%0], [%1], %2, [%3], %4;" ::"r"(dst), "l"(src), "r"(bytes), "r"(bar), "h"((uint16_t)3) : "memory");
}
__device__ __forceinline__ void mbar_arrive_peer(uint32_t bar, uint32_t peer) {
  asm volatile("{\n.reg .b32 r;\nmapa.shared::cluster.u32 r, %0, %1;\nmbarrier.arrive.relaxed.cluster.shared::cluster.b64 _, [r];\n}" ::"r"(bar), "r"(peer) : "memory");
}
__device__ __forceinline__ void mbar_wait_cl(uint32_t bar, uint32_t parity) {
  asm volatile("{\n.reg .pred p,q;\n.reg .u32 c;\nmov.u32 c,0;\nL%=:\nmbarrier.try_wait.parity.relaxed.cluster.shared::cta.b64 p, [%0], %1;\n@p bra D%=;\n"
               "add.u32 c,c,1;\nsetp.gt.u32 q,c,1048576;\n" TRAPS("q", "%0") "bra L%=;\nD%=:\n}" ::"r"(bar), "r"(parity) : "memory");
}
__device__ __forceinline__ void tma2(uint32_t dst, const CUtensorMap* m, int c0, int c1, uint32_t bar) {
  asm volatile("cp.async.bulk.tensor.2d.shared::cluster.global.mbarrier::complete_tx::bytes [%0], [%1, {%3,%4}], [%2];" ::"r"(dst), "l"(m), "r"(bar), "r"(c0), "r"(c1) : "memory");
}
__device__ __forceinline__ void tma3(uint32_t dst, const CUtensorMap* m, int c0, int c1, int c2, uint32_t bar) {
  asm volatile("cp.async.bulk.tensor.3d.shared::cluster.global.mbarrier::complete_tx::bytes [%0], [%1, {%3,%4,%5}], [%2];" ::"r"(dst), "l"(m), "r"(bar), "r"(c0), "r"(c1), "r"(c2) : "memory");
}
__device__ __forceinline__ void tma4(uint32_t dst, const CUtensorMap* m, int c0, int c1, int c2, int c3, uint32_t bar) {
  asm volatile("cp.async.bulk.tensor.4d.shared::cluster.global.mbarrier::complete_tx::bytes [%0], [%1, {%3,%4,%5,%6}], [%2];" ::"r"(dst), "l"(m), "r"(bar), "r"(c0), "r"(c1), "r"(c2), "r"(c3) : "memory");
}
__device__ __forceinline__ void pf_l2(const void* p, uint32_t bytes) { asm volatile("cp.async.bulk.prefetch.L2.global [%0], %1;" ::"l"(p), "r"(bytes) : "memory"); }
__device__ __forceinline__ void fence_async_smem() { asm volatile("fence.proxy.async.shared::cta;" ::: "memory"); }
__device__ __forceinline__ void fence_async_all() { asm volatile("fence.proxy.async;" ::: "memory"); }
__device__ __forceinline__ bool elect() { uint32_t p; asm volatile("{\n.reg .pred P;\nelect.sync _|P, 0xffffffff;\nselp.u32 %0,1,0,P;\n}" : "=r"(p)); return p; }
__device__ __forceinline__ uint32_t clk32() { uint32_t c; asm volatile("mov.u32 %0, %%clock;" : "=r"(c)); return c; }
__device__ __forceinline__ void bar_sync(int id, int n) { asm volatile("bar.sync %0, %1;" ::"r"(id), "r"(n) : "memory"); }
__device__ __forceinline__ bool bar_all(int id, uint32_t v) {
  uint32_t r;
  asm volatile("{\n.reg .pred p,q;\nsetp.ne.u32 p, %2, 0;\nbarrier.cta.red.and.aligned.pred q, %1, 128, p;\nselp.u32 %0, 1, 0, q;\n}" : "=r"(r) : "r"(id), "r"(v) : "memory");
  return r;
}
__device__ __forceinline__ void wg_fence() { asm volatile("wgmma.fence.sync.aligned;" ::: "memory"); }
__device__ __forceinline__ void wg_commit() { asm volatile("wgmma.commit_group.sync.aligned;" ::: "memory"); }
template <int N> __device__ __forceinline__ void wg_wait() { asm volatile("wgmma.wait_group.sync.aligned %0;" ::"n"(N) : "memory"); }
__device__ __forceinline__ void ldsm4t(uint32_t (&r)[4], uint32_t a) {
  asm volatile("ldmatrix.sync.aligned.m8n8.x4.trans.shared.b16 {%0,%1,%2,%3}, [%4];" : "=r"(r[0]), "=r"(r[1]), "=r"(r[2]), "=r"(r[3]) : "r"(a) : "memory");
}
__device__ __forceinline__ void ldsm4(uint32_t (&r)[4], uint32_t a) {
  asm volatile("ldmatrix.sync.aligned.m8n8.x4.shared.b16 {%0,%1,%2,%3}, [%4];" : "=r"(r[0]), "=r"(r[1]), "=r"(r[2]), "=r"(r[3]) : "r"(a) : "memory");
}
__device__ __forceinline__ void stsm4k(uint32_t a, uint32_t r0, uint32_t r1, uint32_t r2, uint32_t r3) {
  asm volatile("stmatrix.sync.aligned.m8n8.x4.shared.b16 [%0], {%1,%2,%3,%4};" ::"r"(a), "r"(r0), "r"(r1), "r"(r2), "r"(r3) : "memory");
}
__device__ __forceinline__ void stsm4(uint32_t a, uint32_t r0, uint32_t r1, uint32_t r2, uint32_t r3) {
  asm volatile("stmatrix.sync.aligned.m8n8.x4.shared.b16 [%0], {%1,%2,%3,%4};" ::"r"(a), "r"(r0), "r"(r1), "r"(r2), "r"(r3) : "memory");
}
__device__ __forceinline__ uint32_t lds32(uint32_t a) { uint32_t v; asm volatile("ld.shared.u32 %0, [%1];" : "=r"(v) : "r"(a) : "memory"); return v; }
__device__ __forceinline__ uint32_t lds16(uint32_t a) { uint32_t v; asm volatile("ld.shared.u16 %0, [%1];" : "=r"(v) : "r"(a) : "memory"); return v; }
__device__ __forceinline__ float ldsf(uint32_t a) { float v; asm volatile("ld.shared.f32 %0, [%1];" : "=f"(v) : "r"(a) : "memory"); return v; }
__device__ __forceinline__ void lds128(uint32_t* v, uint32_t a) { asm volatile("ld.shared.v4.u32 {%0,%1,%2,%3}, [%4];" : "=r"(v[0]), "=r"(v[1]), "=r"(v[2]), "=r"(v[3]) : "r"(a) : "memory"); }
__device__ __forceinline__ void sts32(uint32_t a, uint32_t v) { asm volatile("st.shared.u32 [%0], %1;" ::"r"(a), "r"(v) : "memory"); }
__device__ __forceinline__ void sts16(uint32_t a, uint32_t v) { asm volatile("st.shared.u16 [%0], %1;" ::"r"(a), "r"(v) : "memory"); }
__device__ __forceinline__ void stsf(uint32_t a, float v) { asm volatile("st.shared.f32 [%0], %1;" ::"r"(a), "f"(v) : "memory"); }
__device__ __forceinline__ void sts64(uint32_t a, uint32_t x, uint32_t y) { asm volatile("st.shared.v2.u32 [%0], {%1,%2};" ::"r"(a), "r"(x), "r"(y) : "memory"); }
__device__ __forceinline__ void sts128(uint32_t a, uint32_t x, uint32_t y, uint32_t z, uint32_t w) {
  asm volatile("st.shared.v4.u32 [%0], {%1,%2,%3,%4};" ::"r"(a), "r"(x), "r"(y), "r"(z), "r"(w) : "memory");
}
__device__ __forceinline__ void stg128(void* p, const uint32_t* v) { asm volatile("st.global.v4.u32 [%0], {%1,%2,%3,%4};" ::"l"(p), "r"(v[0]), "r"(v[1]), "r"(v[2]), "r"(v[3]) : "memory"); }
__device__ __forceinline__ uint32_t ldg32(const void* p) { uint32_t v; asm volatile("ld.global.u32 %0, [%1];" : "=r"(v) : "l"(p) : "memory"); return v; }
__device__ __forceinline__ void ldg128(uint32_t* v, const void* p) { asm volatile("ld.global.nc.v4.u32 {%0,%1,%2,%3}, [%4];" : "=r"(v[0]), "=r"(v[1]), "=r"(v[2]), "=r"(v[3]) : "l"(p) : "memory"); }
__device__ __forceinline__ uint32_t lda32(const void* p) { uint32_t v; asm volatile("ld.acquire.gpu.global.u32 %0, [%1];" : "=r"(v) : "l"(p) : "memory"); return v; }
__device__ __forceinline__ uint32_t ldg16(const void* p) { uint32_t v; asm volatile("ld.global.u16 %0, [%1];" : "=r"(v) : "l"(p) : "memory"); return v; }
__device__ __forceinline__ uint32_t pk2(float lo, float hi) { uint32_t r; asm("cvt.rn.bf16x2.f32 %0, %1, %2;" : "=r"(r) : "f"(hi), "f"(lo)); return r; }
__device__ __forceinline__ float bflo(uint32_t v) { return __uint_as_float(v << 16); }
__device__ __forceinline__ float bfhi(uint32_t v) { return __uint_as_float(v & 0xffff0000u); }
__device__ __forceinline__ uint32_t prmt(uint32_t a, uint32_t b, uint32_t s) { uint32_t r; asm("prmt.b32 %0, %1, %2, %3;" : "=r"(r) : "r"(a), "r"(b), "r"(s)); return r; }
__device__ __forceinline__ uint32_t hadd2(uint32_t a, uint32_t b) { uint32_t r; asm("add.rn.bf16x2 %0, %1, %2;" : "=r"(r) : "r"(a), "r"(b)); return r; }
__device__ __forceinline__ uint32_t hmul2(uint32_t a, uint32_t b) { uint32_t r; asm("mul.rn.bf16x2 %0, %1, %2;" : "=r"(r) : "r"(a), "r"(b)); return r; }
__device__ __forceinline__ uint32_t hfma2(uint32_t a, uint32_t b, uint32_t c) { uint32_t r; asm("fma.rn.bf16x2 %0, %1, %2, %3;" : "=r"(r) : "r"(a), "r"(b), "r"(c)); return r; }
__device__ __forceinline__ float ex2f(float x) { float y; asm("ex2.approx.ftz.f32 %0, %1;" : "=f"(y) : "f"(x)); return y; }
__device__ __forceinline__ float rcpf(float x) { float y; asm("rcp.approx.ftz.f32 %0, %1;" : "=f"(y) : "f"(x)); return y; }
__device__ __forceinline__ void stt(const uint4* p, uint32_t x, uint32_t y, uint32_t z, uint32_t w, uint32_t par) {
  asm volatile("{\n.reg .b64 l,h;\n.reg .b128 q;\n.reg .b32 t;\nlop3.b32 t, %1, 0xfffffffe, %5, 0xea;\nmov.b64 l, {t,%2};\nmov.b64 h, {%3,%4};\nmov.b128 q, {l,h};\n"
               "st.relaxed.gpu.global.b128 [%0], q;\n}" ::"l"(p), "r"(x), "r"(y), "r"(z), "r"(w), "r"(par) : "memory");
}
__device__ __forceinline__ void str128(const uint4* p, const uint32_t* t) {
  asm volatile("{\n.reg .b64 l,h;\n.reg .b128 q;\nmov.b64 l, {%1,%2};\nmov.b64 h, {%3,%4};\nmov.b128 q, {l,h};\n"
               "st.relaxed.gpu.global.b128 [%0], q;\n}" ::"l"(p), "r"(t[0]), "r"(t[1]), "r"(t[2]), "r"(t[3]) : "memory");
}
__device__ __forceinline__ uint32_t tag_if(uint32_t v, uint32_t sel, uint32_t par) { uint32_t r; asm("lop3.b32 %0, %1, %2, %3, 0xb8;" : "=r"(r) : "r"(v), "r"(sel), "r"(par)); return r; }
#define LDT_(A, O, R0, R1, R2, R3) "ld.relaxed.gpu.global.b128 q, [" A "+" O "];\nmov.b128 {l,h}, q;\nmov.b64 {" R0 "," R1 "}, l;\nmov.b64 {" R2 "," R3 "}, h;\n"
#define LDT5_ LDT_("%20", "0", "%0", "%1", "%2", "%3") LDT_("%20", "%21", "%4", "%5", "%6", "%7") LDT_("%20", "%22", "%8", "%9", "%10", "%11") \
              LDT_("%20", "%23", "%12", "%13", "%14", "%15") LDT_("%20", "%24", "%16", "%17", "%18", "%19")
#define R20_(C, v) C(v[0]), C(v[1]), C(v[2]), C(v[3]), C(v[4]), C(v[5]), C(v[6]), C(v[7]), C(v[8]), C(v[9]), C(v[10]), C(v[11]), C(v[12]), C(v[13]), C(v[14]), C(v[15]), \
                   C(v[16]), C(v[17]), C(v[18]), C(v[19])
template <int ST> __device__ __forceinline__ void chk5(uint32_t (&v)[20], const uint4* p, uint32_t m) {
  asm volatile("{\n.reg .pred p;\n.reg .b64 l,h;\n.reg .b128 q;\n.reg .b32 a,b,c;\nmov.u32 c, 0;\nL%=:\n"
               "xor.b32 a, %0, %25;\nxor.b32 b, %4, %25;\nand.b32 a, a, b;\nxor.b32 b, %8, %25;\nand.b32 a, a, b;\nxor.b32 b, %12, %25;\nand.b32 a, a, b;\nxor.b32 b, %16, %25;\n"
               "lop3.b32 a, a, b, 1, 0x80;\nsetp.ne.u32 p, a, 0;\nvote.sync.all.pred p, p, 0xffffffff;\n@p bra.uni D%=;\n" LDT5_
               "add.u32 c, c, 1;\nsetp.gt.u32 p, c, 1048576;\n" TRAPS("p", "1") "bra.uni L%=;\nD%=:\n"
               "}"
               : R20_("+r", v) : "l"(p), "n"(ST), "n"(2 * ST), "n"(3 * ST), "n"(4 * ST), "r"(m) : "memory");
}
template <int ST> __device__ __forceinline__ void ld5(uint32_t (&v)[20], const uint4* p) {
  asm volatile("{\n.reg .b64 l,h;\n.reg .b128 q;\n" LDT5_ "}" : R20_("=r", v) : "l"(p), "n"(ST), "n"(2 * ST), "n"(3 * ST), "n"(4 * ST) : "memory");
}
__device__ __forceinline__ void get1w(uint32_t (&v)[4], const uint4* p, uint32_t m, uint32_t j) {
  asm volatile("{\n.reg .pred p,u,w;\n.reg .b64 l,h;\n.reg .b128 q;\n.reg .b32 a,b,c;\nmov.u32 c, 0;\nand.b32 a, %6, 1;\nsetp.ne.u32 u, a, 0;\nsetp.gt.u32 w, %6, 1;\nL%=:\n"
               LDT_("%4", "0", "%0", "%1", "%2", "%3") "selp.b32 a, %1, %0, u;\nselp.b32 b, %3, %2, u;\nselp.b32 a, b, a, w;\nxor.b32 a, a, %5;\nand.b32 a, a, 1;\n"
               "setp.ne.u32 p, a, 0;\nvote.sync.all.pred p, p, 0xffffffff;\n@p bra.uni D%=;\n"
               "add.u32 c, c, 1;\nsetp.gt.u32 p, c, 1048576;\n" TRAPS("p", "4") "bra.uni L%=;\nD%=:\n}"
               : "=&r"(v[0]), "=&r"(v[1]), "=&r"(v[2]), "=&r"(v[3]) : "l"(p), "r"(m), "r"(j) : "memory");
}
template <int ST> __device__ __forceinline__ void poll4(uint32_t (&v)[16], const uint4* p, const uint4* pl, uint32_t m) {
  asm volatile("{\n.reg .pred p;\n.reg .b64 l,h;\n.reg .b128 q;\n.reg .b32 a,b,c;\nmov.u32 c, 0;\nL%=:\n"
               LDT_("%16", "0", "%0", "%1", "%2", "%3") LDT_("%16", "%19", "%4", "%5", "%6", "%7") LDT_("%16", "%20", "%8", "%9", "%10", "%11") LDT_("%17", "0", "%12", "%13", "%14", "%15")
               "xor.b32 a, %0, %18;\nxor.b32 b, %4, %18;\nand.b32 a, a, b;\nxor.b32 b, %8, %18;\nand.b32 a, a, b;\nxor.b32 b, %12, %18;\n"
               "lop3.b32 a, a, b, 1, 0x80;\nsetp.ne.u32 p, a, 0;\nvote.sync.all.pred p, p, 0xffffffff;\n@p bra.uni D%=;\n"
               "add.u32 c, c, 1;\nsetp.gt.u32 p, c, 1048576;\n" TRAPS("p", "2") "bra.uni L%=;\nD%=:\n}"
               : "=r"(v[0]), "=r"(v[1]), "=r"(v[2]), "=r"(v[3]), "=r"(v[4]), "=r"(v[5]), "=r"(v[6]), "=r"(v[7]), "=r"(v[8]), "=r"(v[9]), "=r"(v[10]), "=r"(v[11]),
                 "=r"(v[12]), "=r"(v[13]), "=r"(v[14]), "=r"(v[15])
               : "l"(p), "l"(pl), "r"(m), "n"(ST), "n"(2 * ST) : "memory");
}
__device__ __forceinline__ void str32(const void* p, uint32_t v) { asm volatile("st.relaxed.gpu.global.u32 [%0], %1;" ::"l"(p), "r"(v) : "memory"); }
__device__ __forceinline__ bool eq4(const void* p, uint32_t e) {
  uint32_t a, b, c, d;
  asm volatile("ld.relaxed.gpu.global.v4.u32 {%0,%1,%2,%3}, [%4];" : "=r"(a), "=r"(b), "=r"(c), "=r"(d) : "l"(p) : "memory");
  return ((a ^ e) | (b ^ e) | (c ^ e) | (d ^ e)) == 0;
}
__device__ __forceinline__ uint32_t ldr32(const void* p) { uint32_t v; asm volatile("ld.relaxed.gpu.global.u32 %0, [%1];" : "=r"(v) : "l"(p) : "memory"); return v; }
__device__ __forceinline__ uint32_t get_ep(uint32_t sb) { mbar_wait(sb + OFF_BAR + 8 * B_EP, 0); return lds32(sb + OFF_EP); }
template <int SZ> __device__ __forceinline__ void fence_regs(float (&d)[SZ]) {
#pragma unroll
  for (int i = 0; i < SZ; i++) asm volatile("" : "+f"(d[i])::"memory");
}
template <int V> struct IC { static constexpr int value = V; };
template <int N, int I = 0, class F> __device__ __forceinline__ void sfor(F&& f) {
  if constexpr (I < N) { f(IC<I>{}); sfor<N, I + 1>(f); }
}
__device__ __forceinline__ uint32_t phi2(float a, float b) {
  uint32_t r;
  asm("{\n.reg .b32 e,t;\nmin.bf16x2 e, %1, %3;\nmax.bf16x2 t, %2, %4;\nadd.rn.bf16x2 %0, e, t;\n}"
      : "=r"(r) : "r"(pk2(ex2f(a * 1.4426950408889634f), ex2f(b * 1.4426950408889634f))), "r"(pk2(a, b)), "r"(0x3F803F80u), "r"(0x35863586u));
  return r;
}
__device__ __forceinline__ uint32_t phi2p(uint32_t t) {
  uint32_t r;
  asm("{\n.reg .b32 e,t;\nmin.bf16x2 e, %1, %3;\nmax.bf16x2 t, %2, %4;\nadd.rn.bf16x2 %0, e, t;\n}"
      : "=r"(r) : "r"(pk2(ex2f(bflo(t) * 1.4426950408889634f), ex2f(bfhi(t) * 1.4426950408889634f))), "r"(t), "r"(0x3F803F80u), "r"(0x35863586u));
  return r;
}
#define QE 4
__device__ __forceinline__ float warp_sum(float v) {
#pragma unroll
  for (int o = 16; o; o >>= 1) v += __shfl_xor_sync(~0u, v, o);
  return v;
}

struct Params {
  const __nv_bfloat16 *Are, *Aim, *Bre, *Bim, *Cre, *Cim, *logdt, *dskip, *w, *wo, *gw;
  __nv_bfloat16* out;
};

template <int LAM, int B, int SG> __device__ __forceinline__ void cv_mm(float (&acc)[64], const uint32_t (&a)[4], uint32_t lo) {
  wgmma_rs<32, 0, Lin<16 * (B + LAM)>, DOFF(256 + 1024 * B - 32 * SG, 16), DHI(256, 3), 1>(acc, a, lo);
}
__device__ __forceinline__ int bfb(int x) { return (int)pk2((float)x, 0.f); }
__device__ __forceinline__ uint32_t hsel(int a, int b) { return (uint32_t)(a * 0x22 + b * 0x2200 + 0x1010); }
struct CvSel { uint32_t e, o, c; int y0; };
__device__ __forceinline__ CvSel cv_sel(int ww, int lane) {
  CvSel s;
  const int y = 2 * ww + ((lane >> 2) & 1) - 2 * (lane & 3);
  s.y0 = y;
  s.e = hsel(bfb(1280 + y) - 0x44A0 + 1, bfb(1279 + y) - 0x44A0 + 1);
  s.o = hsel(bfb(1288 + y) - 0x44A1 + 2, bfb(1287 + y) - 0x44A1 + 2);
  const int f = y < -4 ? 3 : 1;
  s.c = hsel(bfb(640 + y) - 0x4420 + f, bfb(639 + y) - 0x4420 + f);
  return s;
}
__device__ __forceinline__ void lds64(uint32_t& x, uint32_t& y, uint32_t a) { asm volatile("ld.shared.v2.u32 {%0,%1}, [%2];" : "=r"(x), "=r"(y) : "r"(a) : "memory"); }
__device__ __forceinline__ void pin4(const uint32_t (&a)[4], uint32_t z) {
  asm volatile("" ::"r"(a[0]), "r"(a[1]), "r"(a[2]), "r"(a[3]), "r"(z) : "memory");
}
struct CvP { uint32_t pa, kd, sp, n0, n1, x0, x1, um; };
struct CvQ { uint32_t kc, kd, sm, s0, tm, t0, va, vb, w0, w1; };
__device__ __forceinline__ void cvp_init(CvP& p, uint32_t tb, uint32_t kb, const CvSel& s, int j) {
  p.pa = tb + 4 * (24 + 136 * j + s.y0); p.kd = kb + 4 * (288 + 8 * j);
  p.sp = lds32(p.pa - 64); p.n0 = lds32(p.pa); p.n1 = lds32(p.pa + 32);
  lds64(p.x0, p.x1, p.kd);
  p.um = prmt(lds32(p.kd - 4), p.x0, s.o);
}
__device__ __forceinline__ void cvq_init(CvQ& p, uint32_t tb, uint32_t kb, const CvSel& s, int j) {
  const uint32_t ax = tb + 4 * (560 + 24 * j + 8 + s.y0);
  p.kc = kb + 4 * (192 + 16 * j) + (s.y0 < -4 ? 0 : 4); p.kd = kb + 4 * (256 + 8 * j);
  p.sm = lds32(ax); p.s0 = lds32(ax + 32); p.tm = lds32(ax + 384); p.t0 = lds32(ax + 416);
  p.va = lds32(p.kc); p.vb = lds32(p.kc + 4);
  lds64(p.w0, p.w1, p.kd);
}
template <int G> __device__ __forceinline__ void cvp_make(CvP& p, const CvSel& s, uint32_t z, uint32_t (&a)[4], uint32_t (&b)[4]) {
  a[0] = p.n0 | z; a[1] = p.n1 | z; a[2] = p.sp ^ z; a[3] = p.n0 ^ z;
  b[0] = prmt(p.x0, p.x1, s.e); b[1] = prmt(p.x0, p.x1, s.o); b[2] = p.um | z; b[3] = b[0] | z;
  p.sp = a[1]; p.um = b[1]; p.x0 = p.x1;
  pin4(a, z); pin4(b, z);
  p.n0 = lds32(p.pa + 64 * G + 64); p.n1 = lds32(p.pa + 64 * G + 96); p.x1 = lds32(p.kd + 4 * G + 8);
}
template <int G> __device__ __forceinline__ void cvq_make(CvQ& p, const CvSel& s, uint32_t z, uint32_t (&a)[4], uint32_t (&b)[4]) {
  const uint32_t vc = lds32(p.kc + 8 * G + 8), vd = lds32(p.kc + 8 * G + 12), w2 = lds32(p.kd + 4 * G + 8);
  a[0] = p.s0 ^ z; a[1] = prmt(p.va, p.vb, s.c); a[2] = p.sm | z; a[3] = p.s0 | z;
  b[0] = p.t0 ^ z; b[1] = prmt(p.w0, p.w1, s.o); b[2] = p.tm | z; b[3] = p.t0 | z;
  p.sm = a[1]; p.tm = b[1];
  pin4(a, z); pin4(b, z);
  p.s0 = prmt(p.vb, vc, s.c); p.t0 = prmt(p.w1, w2, s.e);
  p.va = vc; p.vb = vd; p.w0 = p.w1; p.w1 = w2;
}
template <int G> __device__ __forceinline__ void cvp_mm(float (&acc)[64], const uint32_t (&a)[4], const uint32_t (&b)[4], uint32_t lo) {
  wg_fence();
  cv_mm<0, 3, G>(acc, a, lo); cv_mm<0, 0, G>(acc, a, lo); cv_mm<0, 1, G>(acc, a, lo); cv_mm<3, 0, G>(acc, b, lo); cv_mm<0, 2, G>(acc, a, lo);
  wg_commit();
}
template <int G> __device__ __forceinline__ void cvq_mm(float (&acc)[64], const uint32_t (&a)[4], const uint32_t (&b)[4], uint32_t lo) {
  wg_fence();
  cv_mm<1, 2, G>(acc, a, lo); cv_mm<1, 0, G>(acc, a, lo); cv_mm<1, 1, G>(acc, a, lo); cv_mm<2, 1, G>(acc, b, lo); cv_mm<2, 0, G>(acc, b, lo);
  wg_commit();
}
template <class F> __device__ __forceinline__ void cv_phaseA(float (&acc)[64], uint32_t tb, uint32_t kb, uint32_t lo, const CvSel& s, int lane, F&& hook) {
  const uint32_t z = lds32(tb);
  CvP p;
  cvp_init(p, tb, kb, s, lane >> 3);
  uint32_t a[4][4], b[4][4];
  cvp_make<0>(p, s, z, a[0], b[0]);
  sfor<8>([&](auto SS) {
    constexpr int g = decltype(SS)::value;
    cvp_mm<g>(acc, a[g & 3], b[g & 3], lo);
    if constexpr (g < 7) cvp_make<g + 1>(p, s, z, a[(g + 1) & 3], b[(g + 1) & 3]);
    hook(SS);
    wg_wait<1>();
  });
}
template <int G0, int G1, class F> __device__ __forceinline__ void cv_phaseB(float (&acc)[64], uint32_t tb, uint32_t kb, uint32_t lo, const CvSel& s, int lane, F&& hook) {
  if constexpr (G1 > G0) {
    const uint32_t z = lds32(tb);
    CvQ p;
    uint32_t a[4][4], b[4][4];
    if constexpr (G0 == 0) {
      cvq_init(p, tb, kb, s, lane >> 3);
    } else {
      const int j = lane >> 3;
      p.kc = kb + 4 * (192 + 16 * j) + (s.y0 < -4 ? 0 : 4); p.kd = kb + 4 * (256 + 8 * j);
      const uint32_t va = lds32(p.kc + 8 * G0 - 8), vb = lds32(p.kc + 8 * G0 - 4), w0 = lds32(p.kd + 4 * G0 - 4);
      p.va = lds32(p.kc + 8 * G0); p.vb = lds32(p.kc + 8 * G0 + 4); p.w0 = lds32(p.kd + 4 * G0); p.w1 = lds32(p.kd + 4 * G0 + 4);
      p.sm = prmt(va, vb, s.c); p.tm = prmt(w0, p.w0, s.o); p.s0 = prmt(vb, p.va, s.c); p.t0 = prmt(p.w0, p.w1, s.e);
    }
    cvq_make<G0>(p, s, z, a[G0 & 3], b[G0 & 3]);
    sfor<G1 - G0>([&](auto SS) {
      constexpr int g = G0 + decltype(SS)::value;
      cvq_mm<g>(acc, a[g & 3], b[g & 3], lo);
      if constexpr (g + 1 < G1) cvq_make<g + 1>(p, s, z, a[(g + 1) & 3], b[(g + 1) & 3]);
      hook(IC<g>{});
      wg_wait<1>();
    });
  }
}
#define W2P 1
#define RSF 2
#define W2I 9
#define RK 0
#define TK 4
#define NB1 0
__device__ __forceinline__ void cv_all(float (&acc)[64], uint32_t tb, uint32_t kb, uint32_t lo, const CvSel& s, int lane, uint32_t sig, int pt = 1) {
  const uint32_t z = lds32(tb);
  CvP p; CvQ q;
  cvp_init(p, tb, kb, s, lane >> 3);
  cvq_init(q, tb, kb, s, lane >> 3);
  uint32_t a[4][4], b[4][4];
  cvp_make<0>(p, s, z, a[0], b[0]);
#pragma unroll 1
  for (int it = 0; it < 4; it++) {
    sfor<2>([&](auto SS) {
      constexpr int g = decltype(SS)::value;
      cvp_mm<g>(acc, a[2 * g], b[2 * g], lo);
      cvq_make<g>(q, s, z, a[2 * g + 1], b[2 * g + 1]);
      wg_wait<1>();
      cvq_mm<g>(acc, a[2 * g + 1], b[2 * g + 1], lo);
      cvp_make<g + 1>(p, s, z, a[(2 * g + 2) & 3], b[(2 * g + 2) & 3]);
      wg_wait<1>();
    });
    p.pa += 128; p.kd += 8; q.kc += 16; q.kd += 8; lo -= 4;
    if (it == W2I && sig) mbar_arrive(sig);
    PROFX(93, pt, 93 + it);
  }
}
__device__ __forceinline__ int y_pos(int c) { return 2 * c + ((c >> 2) & 1); }
__device__ __forceinline__ void cv_store(float (&acc)[64], int ch, int ww, int lane, uint32_t stg, uint32_t par, int nb, uint32_t sig = 0) {
  const bool o1 = lane & 8, o2 = lane & 16;
  uint32_t X[8][2];
  {
    uint32_t r[8][2];
#pragma unroll
    for (int p = 0; p < 8; p++)
#pragma unroll
      for (int h = 0; h < 2; h++) r[p][h] = __shfl_xor_sync(~0u, pk2(acc[8 * p + 4 + 2 * h], acc[8 * p + 5 + 2 * h]), 8);
#pragma unroll
    for (int p = 0; p < 8; p++)
#pragma unroll
      for (int h = 0; h < 2; h++) X[p][h] = hadd2(pk2(acc[8 * p + 2 * h], acc[8 * p + 1 + 2 * h]), o1 ? r[p][h] : (p ? r[p - 1][h] : 0u));
  }
  if (W2P == 0 && sig) { asm volatile("" :: "r"(X[7][1])); mbar_arrive(sig); }
  uint32_t r[4][2], w[4][2];
#pragma unroll
  for (int p = 0; p < 4; p++)
#pragma unroll
    for (int h = 0; h < 2; h++) r[p][h] = __shfl_xor_sync(~0u, X[2 * p + 1][h], 16);
#pragma unroll
  for (int p = 0; p < 4; p++)
#pragma unroll
    for (int h = 0; h < 2; h++) w[p][h] = hadd2(X[2 * p][h], o2 ? r[p][h] : (p ? r[p - 1][h] : 0u));
  const uint32_t a = stg + ww * 1024 + lane * 16;
  if (nb) bar_sync(nb, 128);
  stsm4(a, w[0][0], w[0][1], w[1][0], w[1][1]);
  stsm4(a + 512, w[2][0], w[2][1], w[3][0], w[3][1]);
  if (W2P == 1 && sig) mbar_arrive(sig);
  __syncwarp();
  uint32_t t[2][4];
  lds128(t[0], a); lds128(t[1], a + 512);
  const uint4* d = g_y + (4 * (lane >> 4) + ((lane >> 1) & 3)) * 10240 + (((lane & 8) >> 1) + ww) * 160 + (ch ^ (lane & 1));
  stt(d, t[0][0], t[0][1], t[0][2], t[0][3], par);
  stt(d + 8 * 10240, t[1][0], t[1][1], t[1][2], t[1][3], par);
  if (W2P == 2 && sig) mbar_arrive(sig);
}

struct C2 { float x, y; };
__device__ __forceinline__ C2 cmul(C2 a, C2 b) { return C2{fmaf(a.x, b.x, -a.y * b.y), fmaf(a.x, b.y, a.y * b.x)}; }
__device__ __forceinline__ C2 csq(C2 a) { return C2{fmaf(a.x, a.x, -a.y * a.y), (a.x + a.x) * a.y}; }
__device__ __forceinline__ C2 cmulc(C2 a, C2 b) { return C2{fmaf(a.x, b.x, a.y * b.y), fmaf(a.y, b.x, -a.x * b.y)}; }
__device__ __forceinline__ C2 cexp2(float a2, float th) { float m = ex2f(a2); return C2{m * __cosf(th), m * __sinf(th)}; }
__device__ __forceinline__ uint32_t pkc(C2 a) { return pk2(a.x, a.y); }
__device__ __forceinline__ uint32_t hcm(uint32_t a, uint32_t m, uint32_t mp) {
  uint32_t r;
  asm("{\n.reg .b16 l,h;\n.reg .b32 t,u,v;\nmov.b32 {l,h}, %1;\nmov.b32 t, {l,l};\nmov.b32 u, {h,h};\nmul.rn.bf16x2 v, u, %3;\nfma.rn.bf16x2 %0, t, %2, v;\n}" : "=r"(r) : "r"(a), "r"(m), "r"(mp));
  return r;
}
template <int I> __device__ __forceinline__ void kg_mm(float (&D)[20], uint32_t dlo, uint32_t sc) {
  asm volatile("{\n.reg .pred p;\n.reg .b32 t,u;\n.reg .b64 da,db;\nsetp.ne.b32 p, %21, 0;\nadd.u32 t, %20, %22;\nmov.b64 da, {t, %24};\nadd.u32 u, %20, %23;\nmov.b64 db, {u, %24};\n"
               "wgmma.mma_async.sync.aligned.m64n40k16.f32.bf16.bf16 {%0,%1,%2,%3,%4,%5,%6,%7,%8,%9,%10,%11,%12,%13,%14,%15,%16,%17,%18,%19}, da, db, p, 1, 1, 0, 0;\n}\n"
               : "+f"(D[0]), "+f"(D[1]), "+f"(D[2]), "+f"(D[3]), "+f"(D[4]), "+f"(D[5]), "+f"(D[6]), "+f"(D[7]), "+f"(D[8]), "+f"(D[9]), "+f"(D[10]), "+f"(D[11]),
                 "+f"(D[12]), "+f"(D[13]), "+f"(D[14]), "+f"(D[15]), "+f"(D[16]), "+f"(D[17]), "+f"(D[18]), "+f"(D[19])
               : "r"(dlo), "r"(sc), "n"(DOFF((I >> 2) * 8192 + (I & 3) * 32, 16)), "n"(DOFF(16384 + (I >> 2) * 5120 + (I & 3) * 32, 16)), "n"(DHI(1024, 1)));
}

__device__ __forceinline__ float bf2f(__nv_bfloat16 v) { return __bfloat162float(v); }
__device__ __forceinline__ void kg_put(const float (&v)[12], uint32_t kb, int b, int q, bool tail) {
  sts32(kb + 2 * (8 * b + 2 * q + 2), pk2(v[0], v[1]));
  sts32(kb + 2 * (8 * b + 2 * q + 2) + 128, pk2(v[2], v[3]));
  const uint32_t k2 = kb + 2 * (q < 2 ? 258 + 4 * b + 2 * q : 258 + 64 * q + 2 * b);
  sts32(k2, pk2(v[4], v[5]));
  sts32(k2 + (q < 2 ? 64 : 32), pk2(v[6], v[7]));
  if (tail) {
    const uint32_t k3 = kb + 2 * (514 + 64 * (q & 1) + b);
    sts16(k3, pk2(v[8], 0.f)); sts16(k3 + 64, pk2(v[9], 0.f)); sts16(k3 + 16, pk2(v[10], 0.f)); sts16(k3 + 80, pk2(v[11], 0.f));
  }
}

struct LagTab {
  uint32_t ix[9], da;
  __device__ __forceinline__ void init(uint32_t sb, int o) {
      int x0, dst;
      if (o < 64) { x0 = 8 * o; dst = 24 + 136 * (o >> 4) + 8 * (o & 15); }
      else if (o < 67) { x0 = 128 * (o - 64) + 120; dst = 24 + 128 + 136 * (o - 64); }
      else if (o < 70) { x0 = -24; dst = 8 * (o - 67); }
      else { const int a = o - 70, a3 = a / 3; x0 = 128 * (4 + a3) - 16 + 8 * (a - 3 * a3); dst = 560 + 8 * a; }
#pragma unroll
      for (int e = 0; e < 9; e++) {
        const int l = x0 - 1 + e;
        ix[e] = sb + OFF_KB + 2 * (l < 128 ? max(l + 1, 0) : bfb(l) - 0x427f);
      }
      da = sb + OFF_TB + 4 * dst;
  }
  __device__ __forceinline__ void build(int c) {
        uint32_t k[9];
#pragma unroll
        for (int e = 0; e < 9; e++) k[e] = lds16(ix[e] + c * KBS);
        sts128(da + c * TBS, prmt(k[1], k[0], 0x5410), prmt(k[2], k[1], 0x5410), prmt(k[3], k[2], 0x5410), prmt(k[4], k[3], 0x5410));
        sts128(da + c * TBS + 16, prmt(k[5], k[4], 0x5410), prmt(k[6], k[5], 0x5410), prmt(k[7], k[6], 0x5410), prmt(k[8], k[7], 0x5410));
  }
};
template <int KS> __device__ __forceinline__ void g1_step(float (&acc)[120], const uint32_t (&a)[4], uint32_t lo) {
  wgmma_rs<192, 1, Chk<0, 32, 40>, DOFF(16384 + KS * 2048, 8192), DHI(1024, 1), 1>(acc, a, lo);
  wgmma_rs<48, 1, Chk<32, 8, 40>, DOFF(40960 + KS * 512, 2048), DHI(256, 3), 1>(acc, a, lo);
}
#define KGM 0x7E
template <bool KG> __device__ __forceinline__ void gemm1(float (&acc)[120], uint32_t sb, int warp, int lane, bool el) {
  const uint32_t bars = sb + OFF_BAR;
  int st = 0, r = 0; uint32_t ph = 0, pbar = 0;
  const uint32_t ao = (warp * 16 + (lane & 15)) * 128 + (((lane >> 4) ^ (lane & 7)) << 4);
  uint32_t a0[4], a1[4];
  float D[20];
#pragma unroll
  for (int e = 0; e < 20; e++) D[e] = 0.f;
#pragma unroll 1
  for (int it = 0; it < 10; it++) {
    const bool kg = KG && ((KGM >> it) & 1);
    mbar_wait(bars + 8 * (B_FULL + st), ph);
    PROFX(1, warp | lane | (it & 11), 1 + (it >> 2));
    const uint32_t sa = sb + st * STB + ao, lo = ((sb + st * STB) & 0x3FFFF) >> 4;
    wg_wait<1>();
    ldsm4(a0, sa);
    wg_fence();
    g1_step<0>(acc, a0, lo);
    wg_commit();
    wg_wait<1>();
    if (it > 0 && el) mbar_arrive(pbar);
    ldsm4(a1, sa ^ 32);
    if (kg) {
      mbar_wait(bars + 8 * B_KF + 8 * (r & 1), (r >> 1) & 1);
      wg_fence();
      const uint32_t dlo = ((sb + ((r & 1) ? OFF_KY : OFF_KX)) & 0x3FFFF) >> 4;
      kg_mm<0>(D, dlo, r != 0 && r != 3);
      sfor<7>([&](auto I) { kg_mm<decltype(I)::value + 1>(D, dlo, 1); });
    }
    wg_fence();
    g1_step<1>(acc, a1, lo);
    wg_commit();
    wg_wait<1>();
    ldsm4(a0, sa ^ 64);
    wg_fence();
    g1_step<2>(acc, a0, lo);
    wg_commit();
    wg_wait<1>();
    ldsm4(a1, sa ^ 96);
    wg_fence();
    g1_step<3>(acc, a1, lo);
    wg_commit();
    if (kg) {
      fence_regs(D);
      if (el) mbar_arrive(bars + 8 * B_KE + 8 * (r & 1));
      if (r == 2 || r == 5) {
        const bool p = warp >= 2;
        const int q = lane & 3;
        float v[12];
#pragma unroll
        for (int e = 0; e < 8; e++) v[e] = p ? D[12 + e] : D[e];
#pragma unroll
        for (int e = 0; e < 4; e++) v[8 + e] = D[8 + e];
        kg_put(v, sb + OFF_KB + ((r == 2 ? 0 : 2) + p) * KBS, 16 * (warp & 1) + (lane >> 2), q, (q >= 2) == p);
        __syncwarp();
        if (r == 5 && el) mbar_arrive(bars + 8 * B_K0);
      }
      r++;
    }
    pbar = bars + 8 * (it == 8 ? B_SF : B_EMPTY + st);
    if (++st == 3) { st = 0; ph ^= 1; }
  }
  wg_wait<0>();
  if (el) mbar_arrive(pbar);
}

__device__ __forceinline__ int o_grp(int bj, int t) { return t < 4 ? ((bj & 4) ^ 4) + t : t == 4 ? bj ^ 1 : ((bj & 6) ^ 2) + t - 5; }
#define DLY0 0u
#define DLY1 384u
#define DLYS 1152u
#define PCH 0
#define YL1 4
#define YL2 8
#define ROT 0
#define IDS() \
  uint32_t sb, tid_, bx_; \
  asm volatile("mov.u32 %0, %1;" : "=r"(sb) : "r"(smem_u32(smem_raw))); \
  asm volatile("mov.u32 %0, %%tid.x;" : "=r"(tid_)); \
  asm volatile("mov.u32 %0, %%ctaid.x;" : "=r"(bx_)); \
  const uint32_t bars = sb + OFF_BAR; \
  const int tid = (tid_ + ROT) & 511, bi = (bx_ >> 4) * 2 + ((bx_ >> 2) & 1), bj = (bx_ & 3) + ((bx_ >> 1) & 4); \
  const int warp = __shfl_sync(~0u, tid >> 5, 0), lane = tid & 31; \
  const bool el = elect(); \
  (void)bars; (void)bi; (void)bj; (void)warp; (void)lane; (void)el;
#define G1LOAD(it, st) { \
    const uint32_t fb_ = bars + 8 * (B_FULL + (st)), d_ = sb + (st) * STB; \
    mbar_expect_tx(fb_, STB); \
    tma3(d_, &mx, (it) * 64, bi * 8, 0, fb_); \
    tma4(d_ + 16384, &mwb, 0, (it) * 64, 0, bj, fb_); \
    tma4(d_ + 40960, &mws, 64, (it) * 64, 0, bj, fb_); }

#define CLARR() asm volatile("barrier.cluster.arrive.relaxed.aligned;" ::: "memory")
__global__ void __cluster_dims__(2, 1, 1) __launch_bounds__(512, 1)
fused_kernel(const __grid_constant__ CUtensorMap mx, const __grid_constant__ CUtensorMap mwb, const __grid_constant__ CUtensorMap mws,
             const __grid_constant__ CUtensorMap msl, const Params P) {
  const int warp0 = __shfl_sync(~0u, ((threadIdx.x + ROT) & 511) >> 5, 0);
  if (warp0 >= 12) {
    {
      IDS();
      if (warp == 12) {
        PROF(0);
        if (el) {
          asm volatile("{\n.reg .pred q;\nsetp.ne.u32 q, %0, 0;\n@q trap;\n}" ::"r"(sb & 1023));
          mbar_init(bars + 8 * B_FULL, 1);
          asm volatile("fence.mbarrier_init.release.cluster;" ::: "memory");
          G1LOAD(0, 0);
          PROFT(0, 5);
          sfor<B_NUM - 1>([&](auto S) { constexpr int s = decltype(S)::value + 1; mbar_init(bars + 8 * s, bar_count(s)); });
          asm volatile("fence.mbarrier_init.release.cluster;" ::: "memory");
        }
      }
    }
    uint32_t ep0 = 0;
    if (warp0 == 13) ep0 = ldr32(&g_epoch);
    bar_sync(0, 512); CLARR();
    asm volatile("setmaxnreg.dec.sync.aligned.u32 40;");
    IDS();
    if (warp == 13 && el) { sts32(sb + OFF_EP, ep0 + 1); mbar_arrive(bars + 8 * B_EP); }
    if (warp == 12) {
      if (el) {
        const uint32_t t1 = clk32();
#pragma unroll 1
        for (int it = 1; it < 3; it++) {
          while (clk32() - t1 < DLY0 + DLY1 * it) { }
          G1LOAD(it, it);
        }
#pragma unroll 1
        for (int row = 192 + 16 * bj + bi; row < 640; row += 128) pf_l2(P.w + row * 1920, 3840);
        while (clk32() - t1 < DLYS) { }
        const uint32_t sl = bars + 8 * B_SLAB;
        mbar_expect_tx(sl, 20480 + 1280);
        tma4(sb + OFF_UT, &msl, 0, 32 * bi + 4 * bj, 0, 0, sl);
        bulk_g2s(sb + OFF_GW, P.gw, 1280, sl);
      }
      __syncwarp();
      int st = 0; uint32_t ph = 0;
#pragma unroll 1
      for (int it = 3; it < 10; it++) {
        mbar_wait(bars + 8 * (B_EMPTY + st), ph);
        if (el) G1LOAD(it, st);
        __syncwarp();
        if (++st == 3) { st = 0; ph ^= 1; }
      }
      const uint32_t wb = bars + 8 * B_WO, ep = get_ep(sb);
      const char* ws = reinterpret_cast<const char*>(g_wo + bj * 6400); (void)wb; (void)ws;
#pragma unroll 1
      for (uint32_t n = 0; !__all_sync(~0u, lda32(g_fw + bj * 32 + (lane & 15)) == ep); n++)
        if (n > (1u << 20)) TRAPC(14);
      mbar_wait(bars + 8 * (B_EMPTY + 1), 0);
      if (el) {
        fence_async_all();
        mbar_expect_tx(wb, 102400);
        bulk_g2s(sb + STB, ws + STB, OFF_PKV - STB, wb);
      }
      mbar_wait(bars + 8 * B_EMPTY, 1);
      if (el) bulk_g2s(sb, ws, STB, wb);
      __syncwarp();
      asm volatile("barrier.cluster.wait.acquire.aligned;" ::: "memory");
      if (lane < 7) mbar_expect_tx(bars + 8 * (B_OF + lane), 20480);
      PROF(40);
    } else if (warp & 1) {
      const int q = lane & 3, g = lane >> 2, hf = (warp >> 1) & 1;
      const int ii = lane & 7, rr = lane >> 3;
      const uint32_t trow = (ii & 2) + (rr >> 1) + 8 * (rr & 1) + 4 * (ii & 1);
      uint32_t ta = sb + OFF_UT + hf * 10240 + trow * 128 + (((ii >> 2) ^ (trow & 7)) << 4);
      const uint4* xdst = g_xT + (320 * hf + 8 * (q >> 1) + g) * 256 + (8 * bi + bj) * 2 + ((q & 1) ^ (bj >> 2));
      uint32_t gwa = sb + OFF_GW + 2 * (320 * hf + 8 * (q >> 1) + g);
      float ga[8];
#pragma unroll
      for (int e = 0; e < 8; e++) ga[e] = 0.f;
      const uint32_t ep = get_ep(sb), par = ep & 1;
      mbar_wait(bars + 8 * B_SLAB, 0);
      if (!hf) PROF(44);
#pragma unroll 1
      for (int it = 0; it < 5; it++) {
        uint32_t v[4][4];
#pragma unroll
        for (int s = 0; s < 4; s++) ldsm4t(v[s], ta ^ (s * 32));
#pragma unroll
        for (int s = 0; s < 4; s++) stt(xdst + s * 4096, v[s][0], v[s][1], v[s][2], v[s][3], par);
#pragma unroll
        for (int s = 0; s < 4; s++) {
          const float w = bflo(lds16(gwa + s * 32));
#pragma unroll
          for (int e = 0; e < 4; e++) { ga[2 * e] = fmaf(bflo(v[s][e]), w, ga[2 * e]); ga[2 * e + 1] = fmaf(bfhi(v[s][e]), w, ga[2 * e + 1]); }
        }
        xdst += 4 * 4096; gwa += 128; ta += 2048;
      }
      __syncwarp();
      if (el) str32(g_fx + hf * 128 + 16 * bj + bi, ep);
      const bool b4 = lane & 16, b3 = lane & 8, b2 = lane & 4;
      float a[4], c[2];
#pragma unroll
      for (int e = 0; e < 4; e++) a[e] = (b4 ? ga[4 + e] : ga[e]) + __shfl_xor_sync(~0u, b4 ? ga[e] : ga[4 + e], 16);
#pragma unroll
      for (int e = 0; e < 2; e++) c[e] = (b3 ? a[2 + e] : a[e]) + __shfl_xor_sync(~0u, b3 ? a[e] : a[2 + e], 8);
      float t = (b2 ? c[1] : c[0]) + __shfl_xor_sync(~0u, b2 ? c[0] : c[1], 4);
      t += __shfl_xor_sync(~0u, t, 2);
      const int gi = (lane & 1) * 8 + (lane >> 2);
      if (hf) {
        stsf(sb + OFF_GP + 4 * gi, t);
        __syncwarp();
        if (el) mbar_arrive(bars + 8 * B_WOT);
        PROF(45);
      } else {
        PROF(41);
        mbar_wait(bars + 8 * B_WOT, 0);
        t += ldsf(sb + OFF_GP + 4 * gi);
        if (!(lane & 2))
          asm volatile("st.relaxed.gpu.global.u32 [%0], %1;" ::"l"(g_gate + 128 * bi + 16 * bj + gi), "r"((__float_as_uint(__fdividef(1.f, 1.f + __expf(-t))) & ~1u) | par) : "memory");
#pragma unroll
        for (int c = 0; c < 5; c++) sts64(sb + OFF_UT + c * UTS + lane * 8, 0, 0);
        fence_async_smem();
        __syncwarp();
        if (el) mbar_arrive(bars + 8 * B_ZP);
        PROF(46);
      }
      {
#pragma unroll 1
        for (int ch = hf ? 0 : 3; ch < (hf ? 3 : 5); ch++) {
          const int d = 80 * bj + 5 * bi + ch, o = d * 192 + 2 * lane;
          uint32_t w[4][3];
          const __nv_bfloat16* pp[4] = {P.Bre, P.Bim, P.Cre, P.Cim};
#pragma unroll
          for (int e = 0; e < 4; e++)
#pragma unroll
            for (int s = 0; s < 3; s++) w[e][s] = ldg32(pp[e] + o + 64 * s);
          const float dt = bflo(pk2(expf(bflo(ldg16(P.logdt + d))), 0.f)), dsk = bflo(ldg16(P.dskip + d));
          float k0 = 0.f;
#pragma unroll
          for (int s = 0; s < 3; s++) {
            k0 += fmaf(bflo(w[2][s]), dt * bflo(w[0][s]), -bflo(w[3][s]) * (dt * bflo(w[1][s])));
            k0 += fmaf(bfhi(w[2][s]), dt * bfhi(w[0][s]), -bfhi(w[3][s]) * (dt * bfhi(w[1][s])));
          }
          k0 = warp_sum(k0) + dsk;
          if (el) sts32(sb + OFF_KB + ch * KBS, pk2(0.f, k0));
        }
        if (el) mbar_arrive(bars + 8 * B_K0);
        PROFX(54, lane | hf, 54);
      }
    } else {
      const uint32_t ep = get_ep(sb), m = (ep & 1) - 1;
      const uint4* src = g_xT + (80 * bj + 5 * bi) * 256;
      {
        const char* wsrc = reinterpret_cast<const char*>(P.wo + 40 * bi * 640 + 80 * bj);
        char* wdst = reinterpret_cast<char*>(g_wo + bj * 6400 + (bi >> 1) * 800 + (bi & 1) * 80);
        mbar_wait(bars + 8 * B_SLAB, 0);
#pragma unroll 1
        for (int s0 = 0; s0 < 13; s0 += 4) {
          uint32_t t[4][4];
#pragma unroll
          for (int s = 0; s < 4; s++) {
            const int v = min(lane + 32 * (s0 + s), 399), r = v / 10, x = v - 10 * r;
            ldg128(t[s], wsrc + r * 1280 + x * 16);
          }
#pragma unroll
          for (int s = 0; s < 4; s++) {
            const int v = min(lane + 32 * (s0 + s), 399), r = v / 10, x = v - 10 * r;
            stg128(wdst + (x >> 1) * 2560 + r * 32 + (((x ^ (r >> 2)) & 1) << 4), t[s]);
          }
          PROFX(100, lane, 100 + (s0 >> 2));
        }
        __syncwarp();
        if (el) { asm volatile("fence.acq_rel.gpu;" ::: "memory"); str32(g_fw + bj * 32 + bi, ep); }
        PROF(43);
      }
#pragma unroll 1
      for (uint32_t n = 0; !__all_sync(~0u, eq4(g_fx + (bj >> 2) * 128 + 4 * lane, ep)); n++)
        if (n > (1u << 20)) TRAPC(10);
      PROF(49);
      if (el && blockIdx.x == 0) *(volatile uint32_t*)&g_epoch = ep;
      mbar_wait(bars + 8 * B_ZP, 0);
#pragma unroll 1
      for (uint32_t k = 0;; k++) {
        if (el) {
          mbar_expect_tx(bars + 8 * B_UTL, 5 * 4096);
#pragma unroll 1
          for (int c = 0; c < 5; c++) bulk_g2s(sb + OFF_UT + 256 + c * UTS, src + c * 256, 4096, bars + 8 * B_UTL);
        }
        mbar_wait(bars + 8 * B_UTL, k & 1);
        PROFX(122, lane, 122 + min(k, 2u));
        uint32_t ok = 1;
#pragma unroll
        for (int c = 0; c < 2; c++) {
          uint32_t t[20];
#pragma unroll
          for (int s = 0; s < 20; s++) t[s] = lds32(sb + OFF_UT + 256 + ((20 * c + s) >> 3) * UTS + lane * 16 + ((20 * c + s) & 7) * 512);
#pragma unroll
          for (int s = 0; s < 20; s++) ok &= t[s] ^ m;
        }
        if (__all_sync(~0u, ok & 1)) break;
        if (k > (1u << 20)) TRAPC(13);
        fence_async_smem();
      }
      if (el) mbar_arrive(bars + 8 * B_UT);
      PROF(42);
    }
    {
      LagTab lt;
      lt.init(sb, tid - 384);
      mbar_wait(bars + 8 * B_LX, 0);
      if (warp < 14) {
        const uint32_t xa = sb + OFF_XR + (warp & 1) * 128 + lane * 4;
        float v[12];
#pragma unroll
        for (int e = 0; e < 12; e++) v[e] = ldsf(xa + e * 256) + ldsf(xa - 3072 + e * 256);
        kg_put(v, sb + OFF_KB + 4 * KBS, 16 * (warp & 1) + (lane >> 2), lane & 3, (lane & 3) < 2);
      }
      bar_sync(6, 128);
      if (tid - 384 < 94) lt.build(4);
      __syncwarp();
      if (el) mbar_arrive(bars + 8 * B_T1);
    }
    const uint32_t ep = lds32(sb + OFF_EP), par = ep & 1;
    {
      const int t = tid - 384;
      uint32_t a0[4], a1[4];
#pragma unroll
      for (int s = 0; s < 4; s++) {
        const int v = t + 128 * s, R = v / 6, V = v - 6 * R, up = R >= 40, kk = R - 32 * up, hh = R - 40 * up >= 20;
        const int n0 = V < 4 ? 24 * hh + 2 * V : 8 + 2 * V + 4 * hh, n1 = V < 4 ? n0 + 8 : 40;
        const uint32_t b = sb + OFF_KVB + up * 4608 + kk * 32;
        a0[s] = b + (n0 >> 4) * 1536 + ((((n0 >> 3) ^ (kk >> 2)) & 1) << 4) + (n0 & 7) * 2;
        a1[s] = b + (n1 >> 4) * 1536 + ((((n1 >> 3) ^ (kk >> 2)) & 1) << 4) + (n1 & 7) * 2;
      }
      const int v1 = min(8 * (warp - 12) + (lane & 7), 29);
      const uint4* p1 = g_kp + ((bj * 16 + bi) * 16 + 4 * (lane >> 3)) * 30 + v1;
      const uint4* p2 = g_kf + bj * 480 + t;
      mbar_wait(bars + 8 * B_KVR, 0);
      if (warp == 12 && el) bulk_g2s(sb + OFF_PKV, reinterpret_cast<const char*>(g_wo + bj * 6400) + OFF_PKV, 102400 - OFF_PKV, bars + 8 * B_WO);
#pragma unroll
      for (int s = 0; s < 5; s++) sts128(sb + OFF_KVB + min(t + 128 * s, 575) * 16, 0, 0, 0, 0);
      uint32_t v[16];
      poll4<480>(v, p1, p1 + 90, par - 1);
      if (warp == 12) PROF(53);
      float s[4];
#pragma unroll
      for (int e = 0; e < 4; e++) {
        s[e] = (__uint_as_float(v[e]) + __uint_as_float(v[4 + e])) + (__uint_as_float(v[8 + e]) + __uint_as_float(v[12 + e]));
        s[e] += __shfl_xor_sync(~0u, s[e], 8);
        s[e] += __shfl_xor_sync(~0u, s[e], 16);
      }
      if (lane < 8) stt(g_kf + bj * 480 + bi * 30 + v1, __float_as_uint(s[0]), __float_as_uint(s[1]), __float_as_uint(s[2]), __float_as_uint(s[3]), par);
      poll4<2048>(v, p2, p2 + (t < 96 ? 384 : 0), par - 1);
      if (warp == 12) PROF(47);
      bar_sync(5, 128);
#pragma unroll
      for (int s = 0; s < 4; s++)
        if (s < 3 || t < 96) {
          sts32(a0[s], pk2(__uint_as_float(v[4 * s]), __uint_as_float(v[4 * s + 1])));
          sts32(a1[s], pk2(__uint_as_float(v[4 * s + 2]), __uint_as_float(v[4 * s + 3])));
        }
      fence_async_smem();
      __syncwarp();
      if (el) mbar_arrive(bars + 8 * B_KVB);
    }
    if (warp == 12) {
      PROF(48);
      const int r = bj & 1, tq = (lane >> 3) < 2 ? 2 * r + (lane >> 3) : (lane >> 3) == 2 ? 4 : 5 + r;
      const uint32_t* po = g_fo + bi * 64 + 8 * o_grp(bj, tq) + (lane & 7);
      const int tl = lane < 2 ? 2 * r + lane : lane == 2 ? 4 : 5 + r;
      const uint4* src = g_o + (bi * 8 + o_grp(bj, tl)) * 1280;
      const uint32_t dst = sb + OFF_OS + (tl % 5) * 20480, fb = bars + 8 * (B_OF + tl);
      if (el) mbar_expect_tx(bars + 8 * B_YT, 20480);
      mbar_wait(bars + 8 * B_T1, 0);
      mbar_wait(bars + 8 * B_ORDY, 0);
      if (el) mbar_arrive_peer(bars + 8 * B_OE, r ^ 1);
      mbar_wait_cl(bars + 8 * B_OE, 0);
      PROF(52);
      uint32_t seen = 0, done = 0;
#pragma unroll 1
      for (int spin = 0; done != 15; spin++) {
        if (seen != 15) {
          const uint32_t b0 = __ballot_sync(~0u, ldr32(po) == ep);
          seen = __ballot_sync(~0u, lane < 4 && ((b0 >> (8 * lane)) & 255) == 255);
        }
        const uint32_t can = __ballot_sync(~0u, lane < 2 || (lane < 4 && mbar_test(bars + 8 * (B_OE - 1 + lane), 0))) & seen & ~done;
        done |= can;
        if ((can >> lane) & 1) {
          if (lane == 2) bulk_g2s(dst, src, 20480, fb); else bulk_g2s_mc(dst, src, 20480, fb);
          PROFX(55, 0, 55 + lane);
        }
        __syncwarp();
        if (spin > (1 << 21)) TRAPC(11);
      }
      mbar_wait(bars + 8 * B_YD, 0);
      if (el) {
        fence_async_smem();
        bulk_g2s(sb + OFF_YT, g_y + (bi * 8 + bj) * 1280, 20480, bars + 8 * B_YT);
      }
      PROF(51);
    }
  } else if (warp0 >= 8) {
    IDS();
    const int kw = warp - 8, t128 = tid - 256;
    const int d0 = 80 * bj + 5 * bi;
    uint32_t par;
    CvSel cs;
    {
      uint32_t pq4[6][4];
#pragma unroll
      for (int e = 0; e < 6; e++) pq4[e][0] = pq4[e][1] = pq4[e][2] = pq4[e][3] = 0;
      if (kw == 0 && el) {
        const __nv_bfloat16* pp[6] = {P.Are, P.Aim, P.Bre, P.Bim, P.Cre, P.Cim};
        mbar_init(bars + 8 * B_PRM, 1);
        asm volatile("fence.mbarrier_init.release.cluster;" ::: "memory");
        mbar_expect_tx(bars + 8 * B_PRM, 6 * 1920);
#pragma unroll
        for (int e = 0; e < 6; e++) bulk_g2s(sb + OFF_KX + e * 1920, pp[e] + d0 * 192, 1920, bars + 8 * B_PRM);
      }
      const uint32_t ldt = ldg16(P.logdt + d0 + min(lane, 4));
      bar_sync(0, 512); CLARR();
      float dt = 0.f, dtb = 0.f, dtc = 0.f;
      const uint32_t so = (lane >> 3) * 128 + (((lane & 7) ^ (lane >> 3)) << 4);
      uint32_t sa = sb + OFF_KY + (kw >> 1) * 8192 + (kw & 1) * 4096 + so;
      uint32_t sbt = sb + OFF_KY + 16384 + (kw >> 1) * 5120 + (kw & 1) * 3072 + so;
      uint32_t sbu = (sb + OFF_KY + 16384 + (kw >> 1) * 5120 + (kw & 1) * 512 + 2048 + so) ^ ((kw & 1) * 64);
#pragma unroll 1
      for (int r = -1; r < 8; r++) {
        float pr[6];
#pragma unroll
        for (int e = 0; e < 6; e++) {
          pr[e] = __uint_as_float(prmt(pq4[e][0], 0, (r & 1) ? 0x3244 : 0x1044));
          if (r & 1) { pq4[e][0] = pq4[e][1]; pq4[e][1] = pq4[e][2]; pq4[e][2] = pq4[e][3]; }
        }
        if (r == 3 || r == 6) { dt = dtb; dtb = dtc; }
        const float a2 = dt * pr[0] * 1.4426950408889634f, th = dt * pr[1], dl = (r == 7 && kw >= 2) ? 0.f : dt;
        const C2 z1 = cexp2(a2, th), w = cexp2(256.f * a2, 256.f * th);
        const C2 c = cmul(C2{pr[4], pr[5]}, C2{dl * pr[2], dl * pr[3]});
        const C2 z2 = csq(z1), z4 = csq(z2), z8 = csq(z4), z3 = cmul(z2, z1), z16 = csq(z8), z32 = csq(z16);
        const uint32_t p1 = pkc(z1), p2 = pkc(z2), p3 = pkc(z3), m4 = pkc(z4), n4 = pk2(-z4.y, z4.x), m8 = pkc(z8), n8 = pk2(-z8.y, z8.x);
        uint32_t y[8];
        {
          C2 Y[4];
          Y[0] = C2{c.x, -c.y};
          Y[1] = cmulc(Y[0], z8); Y[2] = cmulc(Y[0], z16); Y[3] = cmulc(Y[1], z16);
#pragma unroll
          for (int j = 0; j < 4; j++) { y[j] = pkc(Y[j]); y[4 + j] = pkc(cmulc(Y[j], z32)); }
        }
        PROFX(74, t128, 74 + max(r, 0));
        if (r > 0 && r < 7) {
          fence_async_smem();
          __syncwarp();
          if (el) mbar_arrive(bars + 8 * B_KF + 8 * (~r & 1));
        }
        if (r >= 2) mbar_wait(bars + 8 * B_KE + 8 * (r & 1), ((r - 2) >> 1) & 1);
        stsm4k(sbt, p1, p2, p3, m4);
        stsm4k(sa, y[0], y[1], y[2], y[3]);
        stsm4k((sa ^ 64) + 512, y[4], y[5], y[6], y[7]);
        stsm4k((sbt ^ 64) + 512, hcm(p1, m4, n4), hcm(p2, m4, n4), hcm(p3, m4, n4), m8);
        const C2 z64 = csq(z32), z128 = csq(z64), z192 = cmul(z128, z64);
        auto scaled = [&](const C2& z, uint32_t o) {
          const uint32_t m = pk2(z.x, -z.y), n = pk2(z.y, z.x);
          stsm4k(sa + o, hcm(y[0], m, n), hcm(y[1], m, n), hcm(y[2], m, n), hcm(y[3], m, n));
          stsm4k((sa ^ 64) + 512 + o, hcm(y[4], m, n), hcm(y[5], m, n), hcm(y[6], m, n), hcm(y[7], m, n));
        };
        scaled(z64, 1024);
        const C2 w2 = csq(w), w3 = cmul(w2, w), x16 = cmul(csq(w2), z8);
        const uint32_t q1 = pkc(w), q2 = pkc(w2), q3 = pkc(w3), qz = pkc(cmul(w, z2));
        scaled(z128, 2048);
        stsm4k(sbt + 1024, qz, hcm(q1, m4, n4), hcm(qz, m4, n4), hcm(q1, m8, n8));
        stsm4k((sbt ^ 64) + 1536, hcm(q2, m4, n4), hcm(q2, m8, n8), hcm(q3, m4, n4), hcm(q3, m8, n8));
        scaled(z192, 3072);
        {
          const uint32_t m = pkc(x16), n = pk2(-x16.y, x16.x);
          stsm4k(sbu, m, hcm(q1, m, n), hcm(q2, m, n), hcm(q3, m, n));
        }
        const uint32_t dx = (r & 1) ? OFF_KX - OFF_KY : OFF_KY - OFF_KX;
        sa += dx; sbt += dx; sbu += dx;
        if (r < 0) {
          PROFT(t128, 4);
          const float dtv = bflo(pk2(expf(bflo(ldt)), 0.f));
          dt = __shfl_sync(~0u, dtv, kw & 1); dtb = __shfl_sync(~0u, dtv, 2 + (kw & 1)); dtc = __shfl_sync(~0u, dtv, 4);
          const int u = (kw >> 1) * 32 + lane;
          const uint32_t pa = sb + OFF_KX + (kw & 1) * 384, pc = sb + OFF_KX + 1536 + 2 * t128;
          mbar_wait(bars + 8 * B_PRM, 0);
          PROFT(t128, 6);
#pragma unroll
          for (int e = 0; e < 6; e++) {
            pq4[e][0] = lds32(pa + e * 1920 + 4 * u);
            pq4[e][2] = lds32(pa + e * 1920 + 768 + 4 * u);
            pq4[e][1] = prmt(lds16(pa + e * 1920 + 256 + 2 * u), lds16(pa + e * 1920 + 1024 + 2 * u), 0x5410);
            pq4[e][3] = prmt(lds16(pc + e * 1920), lds16(pc + e * 1920 + (kw < 2 ? 256 : 0)), 0x5410);
          }
          bar_sync(4, 128);
        }
      }
      PROFT(t128, 81);
      float D[20];
#pragma unroll
      for (int e = 0; e < 20; e++) D[e] = 0.f;
      fence_async_smem();
      bar_sync(4, 128);
      fence_regs(D);
      wg_fence();
      sfor<8>([&](auto I) { kg_mm<decltype(I)::value>(D, ((sb + OFF_KX) & 0x3FFFF) >> 4, 1); });
      wg_commit();
      sfor<8>([&](auto I) { kg_mm<decltype(I)::value>(D, ((sb + OFF_KY) & 0x3FFFF) >> 4, 1); });
      wg_commit();
      const bool p = kw >= 2;
      const int q = lane & 3;
      const int o = t128;
      LagTab lt;
      lt.init(sb, o);
      par = get_ep(sb) & 1;
      cs = cv_sel(kw, lane);
      PROFT(t128, 72);
      mbar_wait(bars + 8 * B_K0, 0);
      wg_wait<1>();
      bar_sync(4, 128);
      if (o < 94) { lt.build(0); lt.build(1); lt.build(2); lt.build(3); }
      __syncwarp();
      if (el) mbar_arrive(bars + 8 * B_T0);
      PROFT(t128, 73);
      wg_wait<0>();
      fence_regs(D);
      {
        float v[12];
#pragma unroll
        for (int e = 0; e < 8; e++) v[e] = p ? D[12 + e] : D[e];
#pragma unroll
        for (int e = 0; e < 4; e++) v[8 + e] = D[8 + e];
        const uint32_t xa = sb + OFF_XR + (kw & 1) * 128 + lane * 4;
        bar_sync(4, 128);
#pragma unroll
        for (int e = 0; e < 12; e++) stsf((p ? (e < 8 ? xa : xa ^ 8) : xa - 3072) + e * 256, v[e]);
        __syncwarp();
        if (el) mbar_arrive(bars + 8 * B_LX);
      }
      PROFT(t128, 83);
    }
    mbar_wait(bars + 8 * B_UT, 0);
#pragma unroll 1
    for (int ch = 0; ch < 5; ch += ch ? 1 : 3) {
      PROFX(84, t128, 84 + 3 * (ch >> 1));
      float acc[64];
#pragma unroll
      for (int c = 0; c < 64; c++) acc[c] = 0.f;
      fence_regs(acc);
      const uint32_t tb = sb + OFF_TB + ch * TBS, kb = sb + OFF_KB + ch * KBS, lo = ((sb + OFF_UT + ch * UTS) & 0x3FFFF) >> 4;
      if (ch == 4) mbar_wait(bars + 8 * B_T1, 0);
      cv_all(acc, tb, kb, lo, cs, lane, ch == 4 && el ? bars + 8 * B_W2 : 0, t128 | (ch != PCH));
      wg_wait<0>();
      fence_regs(acc);
      if (ch == 4 && el) mbar_arrive(bars + 8 * (B_OE + 1));
      PROFX(85, t128, 85 + 3 * (ch >> 1));
      cv_store(acc, 1280 * bj + y_pos(5 * bi + ch), kw, lane, sb + OFF_UT + (ch == 4 ? 3 * UTS : 0), par, ch == 4 ? 0 : 4, ch == 4 && el ? bars + 8 * B_W2 : 0);
      __syncwarp();
      if (ch == 4 && el) mbar_arrive(bars + 8 * B_YD);
      PROFX(86, t128, 86 + 3 * (ch >> 1));
    }
  } else {
    bar_sync(0, 512); CLARR();
    asm volatile("setmaxnreg.inc.sync.aligned.u32 168;");
    uint32_t pq[20];
    {
      float acc[120];
      {
        IDS();
        const uint32_t e1 = get_ep(sb) - 1;
        const int r0 = tid / 30, x = tid + 256, r1 = x / 30;
        stt(g_kp + ((bj * 16 + r0) * 16 + bi) * 30 + tid - 30 * r0, e1, e1, e1, e1, e1 & 1);
        stt(x < 480 ? g_kp + ((bj * 16 + r1) * 16 + bi) * 30 + x - 30 * r1 : x < 510 ? g_kf + bj * 480 + bi * 30 + x - 480
                    : reinterpret_cast<const uint4*>(g_fo + (bi * 8 + bj) * 8) + x - 510, e1, e1, e1, e1, e1 & 1);
#pragma unroll
        for (int c = 0; c < 120; c++) acc[c] = 0.f;
        fence_regs(acc);
        if (warp < 4) {
          asm volatile("setmaxnreg.inc.sync.aligned.u32 176;");
          gemm1<true>(acc, sb, warp, lane, el);
          asm volatile("setmaxnreg.dec.sync.aligned.u32 168;");
        } else {
          gemm1<false>(acc, sb, warp, lane, el);
        }
        fence_regs(acc);
      }
      IDS();
      const int wg = warp >> 2, ww = warp & 3, t128 = tid & 127, g = lane >> 2, q = lane & 3;
      const int pb = 8 + wg * 16; (void)pb;
      PROFX(8, tid & 127, pb + 0);
      mbar_wait(bars + 8 * B_SF, 0);
      PROFX(112, tid & 127, 112 + wg);
      const uint32_t row = wg * 64 + ww * 16 + (lane & 7) + ((lane >> 3) & 1) * 8;
      const uint32_t rb = sb + OFF_PKV + row * 128;
#pragma unroll
      for (int cp = 0; cp < 5; cp++) {
        const int c = 2 * cp + (lane >> 4), a = c >= 5, cc = c - 5 * a;
        const uint32_t ad = rb + a * 16384 + ((cc ^ (row & 7)) << 4);
        const float* v = &acc[80 + 8 * cp];
        stsm4(ad + 32768, pk2(v[0], v[1]), pk2(v[2], v[3]), pk2(v[4], v[5]), pk2(v[6], v[7]));
        const float* k = &acc[40 + 8 * cp];
        stsm4(ad, phi2(k[0], k[1]), phi2(k[2], k[3]), phi2(k[4], k[5]), phi2(k[6], k[7]));
      }
      sts128(sb + OFF_PKV + 32768 + wg * 16384 + t128 * 128 + ((5 ^ (t128 & 7)) << 4), 0x3F80u, 0x3F80u, 0x3F80u, 0x3F80u);
      PROFX(114, tid & 127, 114 + wg);
      fence_async_smem();
      PROFX(116, tid & 127, 116 + wg);
      bar_sync(1, 256);
      PROFX(9, tid & 127, pb + 1);
      float kv[24];
#pragma unroll
      for (int c = 0; c < 24; c++) kv[c] = 0.f;
      fence_regs(kv);
      wg_fence();
      {
        const uint32_t alo = ((sb + OFF_PKV + wg * 16384) & 0x3FFFF) >> 4;
        sfor<8>([&](auto KS) {
          constexpr int ks = decltype(KS)::value;
          wgmma_ss<48, 1, 1, Lin<0>, DOFF(ks * 2048, 8192), DHI(1024, 1), DOFF(32768 + ks * 2048, 8192), DHI(1024, 1), 1>(kv, alo, alo);
        });
      }
      wg_commit();
      const uint32_t par = lds32(sb + OFF_EP) & 1;
      const uint4* kd[2];
#pragma unroll
      for (int h = 0; h < 2; h++) {
        const int R = 40 * wg + 16 * ww + g + 8 * h, R5 = R / 5;
        kd[h] = g_kp + ((bj * 16 + R5) * 16 + bi) * 30 + (R - 5 * R5) * 6 + q;
      }
#pragma unroll
      for (int c = 0; c < 20; c++) { pq[c] = c < QE ? phi2(acc[2 * c], acc[2 * c + 1]) : pk2(acc[2 * c], acc[2 * c + 1]); asm volatile("" : "+r"(pq[c])::"memory"); }
      wg_wait<0>();
      fence_regs(kv);
      PROFX(118, tid & 127, 118 + wg);
#pragma unroll
      for (int h = 0; h < 2; h++) {
        const int m = 16 * ww + g + 8 * h;
        const bool hh = m >= 20;
        const float* k = &kv[2 * h];
        if (m < 40) {
          stt(kd[h], __float_as_uint(hh ? k[12] : k[0]), __float_as_uint(hh ? k[13] : k[1]), __float_as_uint(hh ? k[16] : k[4]), __float_as_uint(hh ? k[17] : k[5]), par);
          if ((q >= 2) == hh)
            stt(kd[h] + (hh ? 2 : 4), __float_as_uint(k[8]), __float_as_uint(k[9]), hh ? 0u : __float_as_uint(k[20]), hh ? __float_as_uint(k[20]) : 0u, par);
        }
      }
      __syncwarp();
      if (el) mbar_arrive(bars + 8 * B_KVR);
      PROFX(120, tid & 127, 120 + wg);
    }
    IDS();
    const int wg = warp >> 2, ww = warp & 3;
    const int g = lane >> 2, q = lane & 3;
    const int pb = 8 + wg * 16; (void)pb;
    const uint32_t ep = lds32(sb + OFF_EP), par = ep & 1;
    PROFX(10, tid & 127, pb + 2);
    uint32_t B0[20], gt[2];
    const uint32_t* gp = g_gate + 128 * bi + 16 * g + 2 * warp;
    const int ov = (lane >> 4) * 128 + warp * 16 + (lane & 15);
    const uint4* op = g_o + bi * 8 * 1280 + ov;
    {
      float acc[64];
#pragma unroll
      for (int c = 0; c < 64; c++) acc[c] = 0.f;
      fence_regs(acc);
      const CvSel cs = cv_sel(ww, lane);
      const uint32_t tb = sb + OFF_TB + TBS + wg * TBS, kb = sb + OFF_KB + KBS + wg * KBS, ut = sb + OFF_UT + UTS + wg * UTS, lo = (ut & 0x3FFFF) >> 4;
      mbar_wait(bars + 8 * B_T0, 0);
      mbar_wait(bars + 8 * B_UT, 0);
      cv_phaseA(acc, tb, kb, lo, cs, lane, [&](auto SS) {
        constexpr int g = decltype(SS)::value, c0 = QE + (20 - QE) * g / 8, c1 = QE + (20 - QE) * (g + 1) / 8;
#pragma unroll
        for (int c = c0; c < c1; c++) {
          asm volatile("" : "+r"(pq[c])::"memory");
          pq[c] = phi2p(pq[c]);
          asm volatile("" : "+r"(pq[c])::"memory");
        }
      });
      cv_phaseB<0, NB1>(acc, tb, kb, lo, cs, lane, [&](auto) {});
      wg_wait<0>();
      fence_regs(acc);
      PROFX(11, tid & 127, pb + 3);
      mbar_wait(bars + 8 * B_KVB, 0);
      PROFX(12, tid & 127, pb + 4);
      {
        float o0[24], o1[24];
#pragma unroll
        for (int c = 0; c < 24; c++) { o0[c] = 0.f; o1[c] = 0.f; }
        fence_regs(o0); fence_regs(o1);
        wg_fence();
        const uint32_t klo = ((sb + OFF_KVB) & 0x3FFFF) >> 4;
        sfor<3>([&](auto S) {
          constexpr int s = decltype(S)::value;
          const uint32_t a0[4] = {pq[4 * s], pq[4 * s + 1], pq[4 * s + 2], pq[4 * s + 3]};
          const uint32_t a1[4] = {pq[4 * s + 8], pq[4 * s + 9], pq[4 * s + 10], pq[4 * s + 11]};
          wgmma_rs<48, 1, Lin<0>, DOFF(s * 512, 1536), DHI(256, 3), 1>(o0, a0, klo);
          wgmma_rs<48, 1, Lin<0>, DOFF(4608 + s * 512, 1536), DHI(256, 3), 1>(o1, a1, klo);
        });
        wg_commit();
        wg_wait<0>();
        fence_regs(o0); fence_regs(o1);
        float rd[2][4];
#pragma unroll
        for (int e = 0; e < 4; e++) {
          rd[0][e] = __shfl_sync(~0u, rcpf(o0[20 + e] + 1e-6f), lane & ~3);
          rd[1][e] = __shfl_sync(~0u, rcpf(o1[20 + e] + 1e-6f), lane & ~3);
        }
#pragma unroll
        for (int c = 0; c < 5; c++) {
          const bool hi = c > 2 || (c == 2 && q >= 2);
#pragma unroll
          for (int h = 0; h < 2; h++) {
            const float s0 = hi ? rd[0][2 * h + 1] : rd[0][2 * h], s1 = hi ? rd[1][2 * h + 1] : rd[1][2 * h];
            B0[2 * c + h] = pk2(o0[4 * c + 2 * h] * s0, o0[4 * c + 2 * h + 1] * s0);
            B0[10 + 2 * c + h] = pk2(o1[4 * c + 2 * h] * s1, o1[4 * c + 2 * h + 1] * s1);
          }
        }
#pragma unroll
        for (int e = 0; e < 20; e++) B0[e] = tag_if(B0[e], q == (e & 3), par);
        const uint32_t sa = sb + OFF_OS + warp * 2560 + lane * 16;
#pragma unroll
        for (int s = 0; s < 5; s++) stsm4(sa + s * 512, B0[4 * s], B0[4 * s + 1], B0[4 * s + 2], B0[4 * s + 3]);
        __syncwarp();
        uint32_t T[20];
#pragma unroll
        for (int s = 0; s < 5; s++) lds128(&T[4 * s], sa + s * 512);
#pragma unroll
        for (int s = 0; s < 5; s++) str128(op + bj * 1280 + s * 256, &T[4 * s]);
        __syncwarp();
        if (el) { str32(g_fo + (bi * 8 + bj) * 8 + warp, ep); mbar_arrive(bars + 8 * B_ORDY); }
      }
      PROFX(13, tid & 127, pb + 5);
      fence_regs(acc);
      cv_phaseB<NB1, 8>(acc, tb, kb, lo, cs, lane, [&](auto) {});
      wg_wait<0>();
      fence_regs(acc);
      PROFX(14, tid & 127, pb + 6);
      asm volatile("ld.relaxed.gpu.global.v2.u32 {%0,%1}, [%2];" : "=r"(gt[0]), "=r"(gt[1]) : "l"(gp) : "memory");
      cv_store(acc, 1280 * bj + y_pos(5 * bi + 1 + wg), ww, lane, ut, par, 2 + wg);
      __syncwarp();
      if (el) mbar_arrive(bars + 8 * (B_OE + 1));
    }
    PROFX(15, tid & 127, pb + 7);
    {
      float acc[40];
#pragma unroll
      for (int c = 0; c < 40; c++) acc[c] = 0.f;
      fence_regs(acc);
      const uint32_t wlo = (sb & 0x3FFFF) >> 4, m = par - 1;
      const int f0 = 2 * warp;
      const uint32_t os = sb + OFF_OS + warp * 256;
      const uint4* zp = g_y + ((bi * 8 + bj) * 8 + warp) * 160 + lane;
      auto rs5 = [&](const uint32_t (&A)[20], int c) {
        wg_fence();
        sfor<5>([&](auto KS) {
          constexpr int ks = decltype(KS)::value;
          const uint32_t a[4] = {A[4 * ks], A[4 * ks + 1], A[4 * ks + 2], A[4 * ks + 3]};
          wgmma_rs<80, 1, Lin<0>, DOFF(ks * 512, 2560), DHI(256, 3), 1>(acc, a, wlo + c * 800);
        });
        wg_commit();
      };
      asm volatile("{\n.reg .pred p;\n.reg .b32 a,b,c;\nmov.u32 c, 0;\nL%=:\nxor.b32 a, %0, %3;\nxor.b32 b, %1, %3;\nlop3.b32 a, a, b, 1, 0x80;\nsetp.ne.u32 p, a, 0;\n"
                   "vote.sync.all.pred p, p, 0xffffffff;\n@p bra.uni D%=;\nld.relaxed.gpu.global.v2.u32 {%0,%1}, [%2];\nadd.u32 c, c, 1;\nsetp.gt.u32 p, c, 1048576;\n" TRAPS("p", "3") "bra.uni L%=;\nD%=:\n}"
                   : "+r"(gt[0]), "+r"(gt[1]) : "l"(gp), "r"(m) : "memory");
      const float g0 = __uint_as_float(gt[0]), g1 = __uint_as_float(gt[1]);
      float h[2] = {1.f - g0, 1.f - g1};
      uint32_t oa = os + (lane >> 4) * 2048 + (((lane & 15) ^ (lane >> 4)) << 4), la[5], go[5];
#pragma unroll
      for (int s = 0; s < 5; s++) {
        const int x = lane + 32 * s, row = x / 10, ck = x - 10 * row;
        la[s] = os + ck * 2048 + ((row ^ (ck & 7)) << 4);
        go[s] = ((row & 7) * 16 + (row >> 3)) * 1280 + ck * 16;
        asm volatile("" : "+r"(la[s]), "+r"(go[s]));
      }
      asm volatile("" : "+r"(oa), "+f"(h[0]), "+f"(h[1]));
      mbar_wait(bars + 8 * B_WO, 0);
      mbar_wait(bars + 8 * (B_OE + 1), 0);
      PROFT(tid, 64);
      rs5(B0, bj);
      mbar_wait(bars + 8 * B_W2, 0);
      const uint32_t vb = sb + OFF_OS + ov * 16;
      uint32_t tg[5];
      auto tags = [&](auto T) {
        constexpr int t = decltype(T)::value;
        mbar_wait(bars + 8 * B_OF + 8 * t, 0);
        PROFX(65, tid, 65 + t);
#pragma unroll
        for (int k = 0; k < 5; k++) tg[k] = lds32(vb + (lane >> 3) * 4 + k * 4096 + (t % 5) * 20480);
      };
      tags(IC<0>{});
      sfor<7>([&](auto T) {
        constexpr int t = decltype(T)::value, so = (t % 5) * 20480;
        if (!__all_sync(~0u, ((tg[0] ^ m) & (tg[1] ^ m) & (tg[2] ^ m) & (tg[3] ^ m) & (tg[4] ^ m)) & 1)) {
#pragma unroll 1
          for (int k = 0; k < 5; k++) {
            uint32_t v[4];
            get1w(v, op + o_grp(bj, t) * 1280 + k * 256, m, lane >> 3);
            sts128(vb + k * 4096 + so, v[0], v[1], v[2], v[3]);
          }
          fence_async_smem();
          __syncwarp();
        }
        wg_fence();
        sfor<5>([&](auto KS) {
          constexpr int ks = decltype(KS)::value;
          wgmma_ss<80, 0, 1, Lin<0>, DOFF(OFF_OS + so + ks * 4096, 2048), DHI(128, 0), DOFF(ks * 512, 2560), DHI(256, 3), 1>(acc, wlo + wg * 64, wlo + o_grp(bj, t) * 800);
          if constexpr (ks == RK && t >= 1 && t <= 2) {
            wg_commit();
            wg_wait<1>();
            if (el) mbar_arrive_peer(bars + 8 * (B_OE + 2), t - 1);
          }
          if constexpr (ks == TK && t < 6) tags(IC<t + 1>{});
        });
        wg_commit();
      });
      PROFX(16, tid & 127, pb + 8);
      mbar_wait(bars + 8 * B_YT, 0);
      PROFX(17, tid & 127, pb + 9);
      const uint32_t yb = sb + OFF_YT + warp * 2560, ya = yb + ((lane >> 4) * 8 + (lane & 7)) * 32 + ((((lane >> 3) ^ (lane >> 2)) & 1) << 4);
      uint32_t y[5][4];
      {
        uint32_t ok = ~0u;
#pragma unroll
        for (int cp = 0; cp < 5; cp++) {
          ldsm4t(y[cp], ya + cp * 512);
          ok &= (y[cp][0] ^ m) & (y[cp][1] ^ m);
          ok &= (y[cp][2] ^ m) & (y[cp][3] ^ m);
        }
        if (!__all_sync(~0u, lane >= 4 || (ok & 0x10001) == 0x10001)) {
          PROF(62);
          uint32_t Y[20];
#pragma unroll
          for (int e = 0; e < 20; e++) Y[e] = m ^ 2;
          chk5<512>(Y, zp, m);
#pragma unroll
          for (int s = 0; s < 5; s++) sts128(yb + lane * 16 + s * 512, Y[4 * s], Y[4 * s + 1], Y[4 * s + 2], Y[4 * s + 3]);
          __syncwarp();
#pragma unroll
          for (int cp = 0; cp < 5; cp++) ldsm4t(y[cp], ya + cp * 512);
        }
      }
      PROFX(19, tid & 127, pb + 11);
      float gy[40];
#pragma unroll
      for (int c = 0; c < 20; c++) { gy[2 * c] = ((c & 1) ? g1 : g0) * bflo(y[c >> 2][c & 3]); gy[2 * c + 1] = ((c & 1) ? g1 : g0) * bfhi(y[c >> 2][c & 3]); }
      fence_regs(gy);
      wg_wait<0>();
      fence_regs(acc);
      PROFX(20, tid & 127, pb + 12);
#pragma unroll
      for (int cp = 0; cp < 5; cp++) {
        uint32_t o[4];
#pragma unroll
        for (int e = 0; e < 4; e++) {
          const int c = 8 * cp + 2 * e;
          o[e] = pk2(fmaf(h[e & 1], acc[c], gy[c]), fmaf(h[e & 1], acc[c + 1], gy[c + 1]));
        }
        stsm4((oa ^ (((2 * cp) & 7) << 4)) + cp * 4096, o[0], o[1], o[2], o[3]);
      }
      PROFX(21, tid & 127, pb + 13);
      __syncwarp();
      char* od = reinterpret_cast<char*>(P.out) + (128 * bi + f0) * 1280 + bj * 160;
#pragma unroll
      for (int s = 0; s < 5; s++) {
        uint32_t t[4];
        lds128(t, la[s]);
        stg128(od + go[s], t);
      }
      PROFX(18, tid & 127, pb + 10);
    }
  }
}

static void make_map(PFN_cuTensorMapEncodeTiled_v12000 enc, CUtensorMap* m, const void* p, int rank, const cuuint64_t* dims, const cuuint64_t* strides,
                     const cuuint32_t* box, CUtensorMapSwizzle sw) {
  const cuuint32_t es[4] = {1, 1, 1, 1};
  enc(m, CU_TENSOR_MAP_DATA_TYPE_BFLOAT16, rank, const_cast<void*>(p), dims, strides, box, es, CU_TENSOR_MAP_INTERLEAVE_NONE, sw,
      CU_TENSOR_MAP_L2_PROMOTION_L2_128B, CU_TENSOR_MAP_FLOAT_OOB_FILL_NONE);
}

}

extern "C" void kernel_launch(void* const* d_in, const int* in_sizes, int n_in, void* d_out, int out_size) {
  using namespace gm;
  (void)in_sizes; (void)n_in; (void)out_size;
  void* fn = nullptr;
  cudaDriverEntryPointQueryResult qr;
  cudaGetDriverEntryPoint("cuTensorMapEncodeTiled", &fn, cudaEnableDefault, &qr);
  auto enc = (PFN_cuTensorMapEncodeTiled_v12000)fn;
  CUtensorMap mx, mwb, mws, msl;
  {
    const cuuint64_t d[3] = {640, 128, 16}, s[2] = {20480, 1280};
    const cuuint32_t b[3] = {64, 8, 16};
    make_map(enc, &mx, d_in[0], 3, d, s, b, CU_TENSOR_MAP_SWIZZLE_128B);
  }
  {
    const cuuint64_t d[4] = {80, 640, 3, 8}, s[3] = {3840, 1280, 160};
    const cuuint32_t b0[4] = {64, 64, 3, 1}, b1[4] = {16, 64, 3, 1};
    make_map(enc, &mwb, d_in[10], 4, d, s, b0, CU_TENSOR_MAP_SWIZZLE_128B);
    make_map(enc, &mws, d_in[10], 4, d, s, b1, CU_TENSOR_MAP_SWIZZLE_32B);
  }
  {
    const cuuint64_t d[4] = {64, 512, 4, 10}, s[3] = {5120, 1280, 128};
    const cuuint32_t b[4] = {64, 4, 4, 10};
    make_map(enc, &msl, d_in[0], 4, d, s, b, CU_TENSOR_MAP_SWIZZLE_128B);
  }
  Params P;
  P.Are = (const __nv_bfloat16*)d_in[1]; P.Aim = (const __nv_bfloat16*)d_in[2]; P.Bre = (const __nv_bfloat16*)d_in[3];
  P.Bim = (const __nv_bfloat16*)d_in[4]; P.Cre = (const __nv_bfloat16*)d_in[5]; P.Cim = (const __nv_bfloat16*)d_in[6];
  P.logdt = (const __nv_bfloat16*)d_in[7]; P.dskip = (const __nv_bfloat16*)d_in[8]; P.w = (const __nv_bfloat16*)d_in[10];
  P.wo = (const __nv_bfloat16*)d_in[11]; P.gw = (const __nv_bfloat16*)d_in[12]; P.out = (__nv_bfloat16*)d_out;
  cudaFuncSetAttribute(fused_kernel, cudaFuncAttributeMaxDynamicSharedMemorySize, SMEM_BYTES);
  fused_kernel<<<128, 512, SMEM_BYTES, cudaStreamPerThread>>>(mx, mwb, mws, msl, P);
}
```
